```python
import torch

def _softmax(x, axis=-1):
    return torch.softmax(x, dim=axis)
def _gelu(x):
    return torch.nn.functional.gelu(x, approximate="tanh")
def _silu(x):
    return torch.nn.functional.silu(x)
def _sigmoid(x):
    return torch.sigmoid(x)
def _layernorm(x, axis=-1, eps=1e-5):
    m = x.mean(dim=axis, keepdim=True)
    v = x.var(dim=axis, keepdim=True, unbiased=False)
    return (x - m) / torch.sqrt(v + eps)
def _scatter_add(tgt, idx, src, axis=0):
    return tgt.clone().index_add_(axis, idx, src)
def _segment_sum(src, seg, n):
    out = torch.zeros((n,) + src.shape[1:], dtype=src.dtype)
    return out.index_add_(0, seg, src)
def _pad(x, pw):
    flat = tuple(v for pair in reversed(pw) for v in pair)
    return torch.nn.functional.pad(x, flat)

kernel_name = 'sequential_preLN__mha_block_cached__glu_gated_geglu__decode'

def setup_inputs():

    _w = (lambda a: (lambda t: t.to(torch.bfloat16) if t.is_floating_point() else t)(torch.as_tensor(a)))
    def _A_setup():
        B, Sq, D = 4, 1, 576
        H, Sk, Dh = 32, 8192, 128
        return {
            "x": _w((lambda *s: torch.randn(*s, dtype=torch.bfloat16) * 0.05)(B, Sq, D)),
            "k_cache": _w((lambda *s: torch.randn(*s, dtype=torch.bfloat16) * 1.6)(B, H, Sk, Dh)),
            "v_cache": _w((lambda *s: torch.randn(*s, dtype=torch.bfloat16) * 0.8)(B, H, Sk, Dh)),
            "wq": _w((lambda *s: torch.randn(*s, dtype=torch.bfloat16) * 1.6)(D, H * Dh) * (D ** -0.5)),
            "wo": _w((lambda *s: torch.randn(*s, dtype=torch.bfloat16) * 0.8)(H * Dh, D) * ((H * Dh) ** -0.5)),
        }
    _A_in = _A_setup()

    def _B_setup():
        B, S, Dm, Df = 4, 1, 576, 4608
        return {
            "x": _w((lambda *s: torch.randn(*s, dtype=torch.bfloat16) * 0.05)(B, S, Dm)),
            "w_gate": _w((lambda *s: torch.randn(*s, dtype=torch.bfloat16) * 0.8)(Dm, Df) * (Dm ** -0.5)),
            "w_up": _w((lambda *s: torch.randn(*s, dtype=torch.bfloat16) * 0.8)(Dm, Df) * (Dm ** -0.5)),
            "w_down": _w((lambda *s: torch.randn(*s, dtype=torch.bfloat16) * 0.8)(Df, Dm) * (Df ** -0.5)),
        }
    _B_in = _B_setup()

    return {
        "A_x": _A_in["x"],
        "A_k_cache": _A_in["k_cache"],
        "A_v_cache": _A_in["v_cache"],
        "A_wq": _A_in["wq"],
        "A_wo": _A_in["wo"],
        "B_x": _B_in["x"],
        "B_w_gate": _B_in["w_gate"],
        "B_w_up": _B_in["w_up"],
        "B_w_down": _B_in["w_down"],
    }

def reference(A_x, A_k_cache, A_v_cache, A_wq, A_wo, B_x, B_w_gate, B_w_up, B_w_down):
    def _A_ref(x, k_cache, v_cache, wq, wo):
        B, Sq, D = x.shape
        H, Dh = 32, 128
        q = (lambda x, *d: x.permute(*d))((x @ wq).reshape(B, Sq, H, Dh), 0, 2, 1, 3)
        scores = torch.einsum("bhqd,bhkd->bhqk", q, k_cache) * (Dh ** -0.5)
        p = _softmax(scores, axis=-1)
        o = torch.einsum("bhqk,bhkd->bhqd", p, v_cache)
        return (lambda x, *d: x.permute(*d))(o, 0, 2, 1, 3).reshape(B, Sq, H * Dh) @ wo

    def _B_ref(x, w_gate, w_up, w_down):
        g = torch.einsum("bsd,df->bsf", x, w_gate)
        u = torch.einsum("bsd,df->bsf", x, w_up)
        h = _gelu(g) * u
        return torch.einsum("bsf,fd->bsd", h, w_down)

    x = A_x
    h = x + _A_ref(_layernorm(x, axis=-1), A_k_cache, A_v_cache, A_wq, A_wo)
    h2 = h + _B_ref(_layernorm(h, axis=-1), B_w_gate, B_w_up, B_w_down)
    return h2
```

```cpp
#include <cuda_runtime.h>
#include <cuda_bf16.h>
#include <cuda.h>
#include <stdint.h>

namespace {

constexpr int NB = 4, DM = 576, NH = 32, SK = 8192, DH = 128, DF = 4608;
#define K_SLOTS 3
#define K_SCHED 1
constexpr int KEYS   = 128;
constexpr int IPH    = SK / KEYS;
constexpr int NITEMS = NB * NH * IPH;
constexpr int NS     = K_SLOTS;
constexpr int NSTAT  = (NS + 1) / 2;
constexpr int SLOT   = KEYS * DH * 2;
constexpr int MT     = KEYS / 16;
constexpr int NTHR   = 320;
constexpr int GRID   = 132;
constexpr int NOP    = 128;
constexpr int FC     = 40;
constexpr int NFF    = (DF + FC - 1) / FC;
constexpr int NRED   = DM / 8;
constexpr int WPITCH = DM * 2 + 16;
constexpr int GU_PIECE_ROWS = 192;
constexpr int GU_PIECES = DM / GU_PIECE_ROWS;
constexpr int GU_BOX_BYTES = GU_PIECE_ROWS * FC * 2;
constexpr int NSA    = NS < GU_PIECES ? GU_PIECES : NS;
static_assert(2 * GU_BOX_BYTES <= SLOT, "piece must fit a slot");

constexpr int WROW     = DM * 2;
constexpr int OFF_RING = 0;
constexpr int OFF_WO   = OFF_RING + NSA * SLOT;
constexpr int OFF_DN   = OFF_WO + 32 * WROW;
constexpr int OFF_XN   = OFF_DN + FC * WROW;
constexpr int OFF_X    = OFF_XN + 4 * WPITCH;
constexpr int OFF_COMB = OFF_X + NB * DM * 4;
constexpr int OFF_RED  = OFF_COMB + 8 * 32 * 4 + 32;
constexpr int OFF_ACT  = OFF_RED + 8 * 32 * 4;
constexpr int ACT_PITCH = 112;
constexpr int OFF_BAR  = OFF_ACT + 4 * ACT_PITCH;
constexpr int NBARS    = NS + 6;
constexpr int OFF_MISC = OFF_BAR + NBARS * 8;
constexpr int SMEM_BYTES = OFF_MISC + 64;
constexpr int OFF_WQ   = OFF_WO;
static_assert(OFF_WO % 1024 == 0 && OFF_DN % 1024 == 0 && DM * 64 <= 32 * WROW, "staging");
static_assert(OFF_BAR % 8 == 0 && OFF_COMB % 16 == 0 && OFF_RED % 16 == 0, "align");
static_assert(SMEM_BYTES <= 232448, "smem");

__device__ unsigned int g_ctr_item;
__device__ __align__(128) uint2 g_q[NB * NH * DH / 2];
__device__ __align__(128) uint4 g_ml[NITEMS];
__device__ __align__(128) uint4 g_op[NITEMS * 32];
__device__ __align__(128) uint4 g_p1[NOP * DM];
__device__ __align__(128) uint4 g_h[NB * DM / 4];
__device__ __align__(128) uint4 g_p2[NFF * DM];

#define TS(i) do {} while (0)

__device__ __forceinline__ uint32_t smem_u32(const void* p) { return (uint32_t)__cvta_generic_to_shared(p); }
__device__ __forceinline__ void mbar_init(uint32_t bar, uint32_t cnt) { asm volatile("mbarrier.init.shared::cta.b64 [%0], %1;" ::"r"(bar), "r"(cnt) : "memory"); }
__device__ __forceinline__ void mbar_expect_tx(uint32_t bar, uint32_t bytes) { asm volatile("mbarrier.arrive.expect_tx.shared::cta.b64 _, [%0], %1;" ::"r"(bar), "r"(bytes) : "memory"); }
__device__ __forceinline__ bool mbar_try(uint32_t bar, uint32_t parity) {
    uint32_t ok;
    asm volatile("{\n.reg .pred p;\nmbarrier.try_wait.parity.shared::cta.b64 p, [%1], %2;\nselp.u32 %0, 1, 0, p;\n}" : "=r"(ok) : "r"(bar), "r"(parity) : "memory");
    return ok != 0;
}
__device__ __forceinline__ void mbar_wait(uint32_t bar, uint32_t parity) {
    uint32_t n = 0;
    while (!mbar_try(bar, parity)) { if (++n > (1u << 24)) __trap(); }
}
__device__ __forceinline__ void bulk_load(uint32_t dst, const void* src, uint32_t bytes, uint32_t bar, uint64_t pol) {
    asm volatile("cp.async.bulk.shared::cluster.global.mbarrier::complete_tx::bytes.L2::cache_hint [%0], [%1], %2, [%3], %4;"
                 ::"r"(dst), "l"(src), "r"(bytes), "r"(bar), "l"(pol) : "memory");
}
__device__ __forceinline__ void tensor_load_2d(uint32_t dst, const CUtensorMap* tm, int c0, int c1, uint32_t bar) {
    asm volatile("cp.async.bulk.tensor.2d.shared::cluster.global.mbarrier::complete_tx::bytes [%0], [%1, {%3, %4}], [%2];"
                 ::"r"(dst), "l"(tm), "r"(bar), "r"(c0), "r"(c1) : "memory");
}
__device__ __forceinline__ void tensor_load_3d(uint32_t dst, const CUtensorMap* tm, int row, uint32_t bar, uint64_t pol) {
    asm volatile("cp.async.bulk.tensor.3d.shared::cluster.global.mbarrier::complete_tx::bytes.L2::cache_hint [%0], [%1, {%3, %3, %4}], [%2], %5;"
                 ::"r"(dst), "l"(tm), "r"(bar), "r"(0), "r"(row), "l"(pol) : "memory");
}
__device__ __forceinline__ void ldsm4(uint32_t (&r)[4], uint32_t addr) {
    asm volatile("ldmatrix.sync.aligned.m8n8.x4.shared.b16 {%0,%1,%2,%3}, [%4];" : "=r"(r[0]), "=r"(r[1]), "=r"(r[2]), "=r"(r[3]) : "r"(addr) : "memory");
}
__device__ __forceinline__ void ldsm4t(uint32_t (&r)[4], uint32_t addr) {
    asm volatile("ldmatrix.sync.aligned.m8n8.x4.trans.shared.b16 {%0,%1,%2,%3}, [%4];" : "=r"(r[0]), "=r"(r[1]), "=r"(r[2]), "=r"(r[3]) : "r"(addr) : "memory");
}
__device__ __forceinline__ void mma16816(float (&c)[4], const uint32_t (&a)[4], uint32_t b0, uint32_t b1) {
    asm volatile("mma.sync.aligned.m16n8k16.row.col.f32.bf16.bf16.f32 {%0,%1,%2,%3}, {%4,%5,%6,%7}, {%8,%9}, {%0,%1,%2,%3};"
                 : "+f"(c[0]), "+f"(c[1]), "+f"(c[2]), "+f"(c[3]) : "r"(a[0]), "r"(a[1]), "r"(a[2]), "r"(a[3]), "r"(b0), "r"(b1));
}
__device__ __forceinline__ float bfr(float x) { return __bfloat162float(__float2bfloat16_rn(x)); }
__device__ __forceinline__ uint32_t pack_bf16(float lo, float hi) {
    uint32_t r; asm("cvt.rn.bf16x2.f32 %0, %1, %2;" : "=r"(r) : "f"(hi), "f"(lo)); return r;
}
__device__ __forceinline__ float bf_lo(uint32_t u) { return __uint_as_float(u << 16); }
__device__ __forceinline__ float bf_hi(uint32_t u) { return __uint_as_float(u & 0xffff0000u); }
__device__ __forceinline__ float ex2(float x) { float r; asm("ex2.approx.ftz.f32 %0, %1;" : "=f"(r) : "f"(x)); return r; }
__device__ __forceinline__ void st_pkt_if(uint32_t on, void* p, uint32_t a, uint32_t b, uint32_t c, uint32_t d) {
    asm volatile("{\n.reg .pred p;\n.reg .b64 l, h;\n.reg .b128 v;\nsetp.ne.u32 p, %5, 0;\nmov.b64 l, {%1,%2};\nmov.b64 h, {%3,%4};\nmov.b128 v, {l,h};\n"
                 "@p st.relaxed.gpu.global.b128 [%0], v;\n}" ::"l"(p), "r"(a), "r"(b), "r"(c), "r"(d), "r"(on) : "memory");
}
__device__ __forceinline__ void ld_pkt_if(uint32_t on, uint4& v, const void* p) {
    asm volatile("{\n.reg .pred p;\n.reg .b64 l, h;\n.reg .b128 v;\nsetp.ne.u32 p, %5, 0;\nmov.b64 l, {%0,%1};\nmov.b64 h, {%2,%3};\nmov.b128 v, {l,h};\n"
                 "@p ld.relaxed.gpu.global.b128 v, [%4];\nmov.b128 {l,h}, v;\nmov.b64 {%0,%1}, l;\nmov.b64 {%2,%3}, h;\n}"
                 : "+r"(v.x), "+r"(v.y), "+r"(v.z), "+r"(v.w) : "l"(p), "r"(on) : "memory");
}
__device__ __forceinline__ void st_pkt8(void* p, uint32_t a, uint32_t b) {
    asm volatile("{\n.reg .b64 v;\nmov.b64 v, {%1,%2};\nst.relaxed.gpu.global.b64 [%0], v;\n}" ::"l"(p), "r"(a), "r"(b) : "memory");
}
__device__ __forceinline__ uint2 ld_pkt8(const void* p) {
    uint2 v;
    asm volatile("{\n.reg .b64 v;\nld.relaxed.gpu.global.b64 v, [%2];\nmov.b64 {%0,%1}, v;\n}" : "=r"(v.x), "=r"(v.y) : "l"(p) : "memory");
    return v;
}
__device__ __forceinline__ void st_f4_if(uint32_t on, void* p, float a, float b, float c, float d, uint32_t tag) {
    const uint32_t ud = __float_as_uint(d);
    st_pkt_if(on, p, __byte_perm(__float_as_uint(a), ud, 0x3217), __byte_perm(__float_as_uint(b), ud, 0x3216),
              __byte_perm(__float_as_uint(c), ud, 0x3215), tag);
}
__device__ __forceinline__ float4 unpack_f4(const uint4& v) {
    const uint32_t d = __byte_perm(__byte_perm(v.z, v.y, 0x0400), v.x, 0x4210);
    return make_float4(__uint_as_float(v.x & 0xffffff00u), __uint_as_float(v.y & 0xffffff00u), __uint_as_float(v.z & 0xffffff00u), __uint_as_float(d & 0xffffff00u));
}
template <int N, bool W, class AddrFn>
__device__ __forceinline__ void poll_pkts(uint4 (&v)[N], const uint32_t (&want)[N], uint32_t tag, AddrFn addr) {
    uint32_t need[N];
#pragma unroll
    for (int i = 0; i < N; i++) { v[i] = make_uint4(0u, 0u, 0u, 0u); need[i] = want[i]; }
    uint32_t n = 0;
    while (true) {
#pragma unroll
        for (int i = 0; i < N; i++) ld_pkt_if(need[i], v[i], addr(i));
        uint32_t any = 0;
#pragma unroll
        for (int i = 0; i < N; i++) { need[i] = ((W ? v[i].w : v[i].z) != tag) ? need[i] : 0u; any |= need[i]; }
        if (!__any_sync(0xffffffffu, any != 0)) break;
        if (++n > (1u << 22)) __trap();
    }
}
template <int ID, int N> __device__ __forceinline__ void bar_sync() { asm volatile("bar.sync %0, %1;" ::"n"(ID), "n"(N) : "memory"); }
template <int ID, int N> __device__ __forceinline__ void bar_arrive() { asm volatile("bar.arrive %0, %1;" ::"n"(ID), "n"(N) : "memory"); }
constexpr int BAR_W = 1;
constexpr int BAR_GO = 2;
constexpr int BAR_FREE = 3;
constexpr int BAR_Q = 8;
__device__ __forceinline__ float warp_sum(float v) {
#pragma unroll
    for (int o = 16; o > 0; o >>= 1) v += __shfl_xor_sync(0xffffffffu, v, o);
    return v;
}
__device__ __forceinline__ float warp_max(float v) {
#pragma unroll
    for (int o = 16; o > 0; o >>= 1) v = fmaxf(v, __shfl_xor_sync(0xffffffffu, v, o));
    return v;
}
__device__ __forceinline__ void layernorm_store(const float4 (&v)[5], int lane, uint8_t* dst) {
    float s = 0.f;
#pragma unroll
    for (int j = 0; j < 5; j++) s += (v[j].x + v[j].y) + (v[j].z + v[j].w);
    const float mean = warp_sum(s) * (1.0f / DM);
    float ss = 0.f;
#pragma unroll
    for (int j = 0; j < 5; j++) {
        const float a = v[j].x - mean, b = v[j].y - mean, c = v[j].z - mean, d = v[j].w - mean;
        const float q = (a * a + b * b) + (c * c + d * d);
        if (j < 4 || lane < 16) ss += q;
    }
    const float var = bfr(warp_sum(ss) * (1.0f / DM));
    const float mb = bfr(mean);
    const float rs = 1.0f / bfr(sqrtf(bfr(var + 1e-5f)));
#pragma unroll
    for (int j = 0; j < 5; j++) {
        uint2 o;
        o.x = pack_bf16(bfr(v[j].x - mb) * rs, bfr(v[j].y - mb) * rs);
        o.y = pack_bf16(bfr(v[j].z - mb) * rs, bfr(v[j].w - mb) * rs);
        if (j < 4 || lane < 16) *reinterpret_cast<uint2*>(dst + (lane + 32 * j) * 8) = o;
    }
}
__device__ __forceinline__ void send_tile(uint32_t on, uint4* dst, const float (&c)[4], int g, int t, uint32_t tag) {
    const float r0 = __shfl_xor_sync(0xffffffffu, (t == 0) ? c[2] : c[0], 1);
    const float r1 = __shfl_xor_sync(0xffffffffu, (t == 0) ? c[3] : c[1], 1);
    st_f4_if((t < 2) ? on : 0u, dst + g + 8 * t, (t == 0) ? c[0] : r0, (t == 0) ? c[1] : r1, (t == 0) ? r0 : c[2], (t == 0) ? r1 : c[3], tag);
}
template <int NSRC>
__device__ __forceinline__ void reduce_cols(uint32_t on, const uint4* src, float* s_red, int vw, int lane, uint32_t tag) {
    uint4 v[4];
    uint32_t want[4];
    const int c0 = vw * 4 + (lane >> 3);
#pragma unroll
    for (int i = 0; i < 4; i++) want[i] = (c0 + 32 * i < NSRC) ? on : 0u;
    poll_pkts<4, true>(v, want, tag, [&](int i) { return src + (c0 + 32 * i) * DM + (lane & 7); });
    float4 a = make_float4(0.f, 0.f, 0.f, 0.f);
#pragma unroll
    for (int i = 0; i < 4; i++) { const float4 f = unpack_f4(v[i]); a.x += f.x; a.y += f.y; a.z += f.z; a.w += f.w; }
#pragma unroll
    for (int o = 8; o <= 16; o <<= 1) {
        a.x += __shfl_xor_sync(0xffffffffu, a.x, o); a.y += __shfl_xor_sync(0xffffffffu, a.y, o);
        a.z += __shfl_xor_sync(0xffffffffu, a.z, o); a.w += __shfl_xor_sync(0xffffffffu, a.w, o);
    }
    if (lane < 8) reinterpret_cast<float4*>(s_red + vw * 32)[lane] = a;
}

struct Params {
    const __nv_bfloat16* x;
    const char* k;
    const char* v;
    __nv_bfloat16* out;
};

__global__ void __launch_bounds__(NTHR, 1)
fused_decode_kernel(const Params p, const __grid_constant__ CUtensorMap tm_q, const __grid_constant__ CUtensorMap tm_o,
                    const __grid_constant__ CUtensorMap tm_gate, const __grid_constant__ CUtensorMap tm_up,
                    const __grid_constant__ CUtensorMap tm_dn) {
    extern __shared__ __align__(1024) uint8_t smem[];
    const uint32_t sb = smem_u32(smem);
    const int tid = threadIdx.x, warp = tid >> 5, lane = tid & 31, cta = blockIdx.x;
    const int g = lane >> 2, t = lane & 3, id = lane >> 3, rr = lane & 7;
    const uint32_t bar_ring = sb + OFF_BAR, bar_wq = bar_ring + NS * 8, bar_wo = bar_wq + 8, bar_gu = bar_wq + 16, bar_dn = bar_wq + 40;
    volatile int* s_misc = reinterpret_cast<volatile int*>(smem + OFF_MISC);
    float* s_x = reinterpret_cast<float*>(smem + OFF_X);
    uint64_t pol;
    asm volatile("createpolicy.fractional.L2::evict_first.b64 %0, 1.0;" : "=l"(pol));

    if (tid == 0) {
        TS(0);
#pragma unroll
        for (int i = 0; i <= NS; i++) mbar_init(bar_ring + i * 8, 1);
        asm volatile("fence.mbarrier_init.release.cluster;" ::: "memory");
        asm volatile("fence.proxy.async.shared::cta;" ::: "memory");
        if (cta < NOP) {
            mbar_expect_tx(bar_wq, DM * 64);
#pragma unroll
            for (int i = 0; i < 3; i++) tensor_load_2d(sb + OFF_WQ + i * 192 * 64, &tm_q, cta * 32, i * 192, bar_wq);
        }
#pragma unroll
        for (int n = 0; n < NS; n++) {
            mbar_expect_tx(bar_ring + n * 8, SLOT);
            bulk_load(sb + OFF_RING + n * SLOT, ((n & 1) ? p.v : p.k) + (size_t)((n >> 1) * GRID + cta) * SLOT, SLOT, bar_ring + n * 8, pol);
        }
    }
    float4 xv[5];
    if (warp >= 6) {
#pragma unroll
        for (int j = 0; j < 5; j++) {
            uint2 u = make_uint2(0u, 0u);
            if (j < 4 || lane < 16) u = __ldg(reinterpret_cast<const uint2*>(p.x + (warp - 6) * DM) + lane + 32 * j);
            xv[j] = make_float4(bf_lo(u.x), bf_hi(u.x), bf_lo(u.y), bf_hi(u.y));
        }
    } else if (warp == 1) {
        if (lane == 0) {
            unsigned int c;
            asm volatile("ld.relaxed.gpu.global.u32 %0, [%1];" : "=r"(c) : "l"(&g_ctr_item) : "memory");
            s_misc[0] = (int)(c / NITEMS + 1);
        } else if (lane < 6) {
            mbar_init(bar_wq + lane * 8, 1);
            asm volatile("fence.mbarrier_init.release.cluster;" ::: "memory");
            s_misc[lane] = (int)sb;
        }
        for (int i = lane; i < ACT_PITCH; i += 32) reinterpret_cast<uint32_t*>(smem + OFF_ACT)[i] = 0u;
    }
    __syncthreads();
    const uint32_t tag = (uint32_t)s_misc[0];

    if (warp == 0) {
        uint32_t offK[4], offV[4];
#pragma unroll
        for (int j = 0; j < 4; j++) {
            offK[j] = sb + OFF_RING + ((id & 1) * 8 + rr) * 256 + (((2 * j + (id >> 1)) ^ rr) << 4);
            offV[j] = sb + OFF_RING + ((id >> 1) * 8 + rr) * 256 + (((2 * j + (id & 1)) ^ rr) << 4);
        }
        const bool valid = (t == (g >> 1));
        const int odd = g & 1;
        const float SCALE = 0.08838834764831845f, LOG2E = 1.4426950408889634f;
        uint32_t it0 = cta, it1 = (NSTAT > 1) ? GRID + cta : 0u, it2 = 0u;
        uint32_t slot = 0, ph = 0, nfree = 0;
        auto claim = [&]() -> uint32_t { uint32_t v = 0; if (lane == 0) v = (atomicAdd(&g_ctr_item, 1u) % NITEMS) + NSTAT * GRID; return v; };
        auto load_q = [&](uint2 (&qq)[16], uint32_t item) {
            const uint2* qp = g_q + (min(item, (uint32_t)NITEMS - 1) / IPH) * (DH / 2) + t;
#pragma unroll
            for (int c = 0; c < 16; c++) qq[c] = ld_pkt8(qp + ((c ^ g) << 2));
        };
        auto refill = [&](const char* base, uint32_t item) {
            if (item < (uint32_t)NITEMS) {
                if (lane == 0) { mbar_expect_tx(bar_ring + slot * 8, SLOT); bulk_load(sb + OFF_RING + slot * SLOT, base + (size_t)item * SLOT, SLOT, bar_ring + slot * 8, pol); }
            } else {
                if (nfree == 0) { if (lane == 0) { s_misc[1] = (int)slot; TS(2); } bar_arrive<BAR_GO, 288>(); }
                asm volatile("bar.arrive %0, 64;" ::"r"(BAR_FREE + nfree) : "memory");
                nfree++;
            }
            if (++slot == NS) { slot = 0; ph ^= 1; }
        };
        uint2 qn[16];
        uint32_t pend = 0;
        if (NS == 2) pend = claim();
        mbar_wait(bar_ring, 0);
        load_q(qn, it0);
        while (true) {
            uint32_t qf[16];
            for (uint32_t n = 0;; n++) {
                uint32_t bad = 0;
#pragma unroll
                for (int c = 0; c < 16; c++) { qf[c] = qn[c].x; bad |= qn[c].y ^ tag; }
                if (!__any_sync(0xffffffffu, bad != 0)) break;
                if (n > (1u << 22)) __trap();
                load_q(qn, it0);
            }
            if (NS == 3) { if (it1 < (uint32_t)NITEMS) pend = claim(); load_q(qn, it1); }
            if (NS == 4) { load_q(qn, it1); }
            mbar_wait(bar_ring + slot * 8, ph);
            float sc[MT][4];
#pragma unroll
            for (int m = 0; m < MT; m++) { sc[m][0] = sc[m][1] = sc[m][2] = sc[m][3] = 0.f; }
            {
                const uint32_t so = slot * SLOT;
#pragma unroll
                for (int j = 0; j < 8; j++) {
#pragma unroll
                    for (int m = 0; m < MT; m++) {
                        uint32_t a[4];
                        ldsm4(a, offK[j & 3] + so + m * 4096 + (j >> 2) * 128);
                        mma16816(sc[m], a, qf[2 * j], qf[2 * j + 1]);
                    }
                }
            }
            if (NS == 2) { it1 = __shfl_sync(0xffffffffu, pend, 0); refill(p.k, it1); if (it1 < (uint32_t)NITEMS) pend = claim(); load_q(qn, it1); }
            if (NS == 3) { __syncwarp(); refill(p.v, it1); }
            if (NS == 4) {
                if (it0 < GRID) pend = claim();
                it2 = (it1 < (uint32_t)NITEMS) ? __shfl_sync(0xffffffffu, pend, 0) : (uint32_t)NITEMS;
                refill(p.k, it2);
            }
            float s[2 * MT];
            float mx = -INFINITY;
#pragma unroll
            for (int m = 0; m < MT; m++) {
                s[2 * m]     = bfr(bfr(odd ? sc[m][1] : sc[m][0]) * SCALE);
                s[2 * m + 1] = bfr(bfr(odd ? sc[m][3] : sc[m][2]) * SCALE);
                mx = fmaxf(mx, fmaxf(s[2 * m], s[2 * m + 1]));
            }
            mx = warp_max(valid ? mx : -INFINITY);
            const float mref = (mx == -INFINITY) ? 0.f : mx;
            float l = 0.f;
            uint32_t pb[2 * MT];
#pragma unroll
            for (int i = 0; i < 2 * MT; i++) {
                const float e = valid ? ex2((s[i] - mref) * LOG2E) : 0.f;
                l += e;
                pb[i] = pack_bf16(e, 0.f) << (odd * 16);
            }
            l = warp_sum(l);
            st_pkt_if(lane == 0, &g_ml[it0], __float_as_uint(mx), __float_as_uint(l), tag, 0u);
            float acc[8][4];
#pragma unroll
            for (int i = 0; i < 8; i++) { acc[i][0] = acc[i][1] = acc[i][2] = acc[i][3] = 0.f; }
            mbar_wait(bar_ring + slot * 8, ph);
            {
                const uint32_t so = slot * SLOT;
#pragma unroll
                for (int m = 0; m < MT; m++) {
#pragma unroll
                    for (int i = 0; i < 8; i++) {
                        uint32_t a[4];
                        ldsm4t(a, offV[i & 3] + so + m * 4096 + (i >> 2) * 128);
                        mma16816(acc[i], a, pb[2 * m], pb[2 * m + 1]);
                    }
                }
            }
            if (NS == 2) { __syncwarp(); refill(p.v, it1); }
            if (NS == 3) { it2 = (it1 < (uint32_t)NITEMS) ? __shfl_sync(0xffffffffu, pend, 0) : (uint32_t)NITEMS; if (nfree < NS) refill(p.k, it2); }
            if (NS == 4) { __syncwarp(); refill(p.v, it2); if (it2 < (uint32_t)NITEMS) pend = claim(); }
            float T[16];
#pragma unroll
            for (int i = 0; i < 8; i++) { T[2 * i] = acc[i][0] + acc[i][3]; T[2 * i + 1] = acc[i][2] + acc[i][1]; }
            float U[16];
#pragma unroll
            for (int c = 0; c < 16; c++) if (!(c & 2)) U[c] = T[c] + __shfl_xor_sync(0xffffffffu, T[c ^ 2], 1);
            const float y0 = U[0] + __shfl_xor_sync(0xffffffffu, U[4], 2), y1 = U[1] + __shfl_xor_sync(0xffffffffu, U[5], 2);
            const float y2 = U[8] + __shfl_xor_sync(0xffffffffu, U[12], 2), y3 = U[9] + __shfl_xor_sync(0xffffffffu, U[13], 2);
            st_f4_if(1u, g_op + (size_t)it0 * 32 + t * 8 + g, y0, y1, y2, y3, tag);
            if (it1 >= (uint32_t)NITEMS) break;
            it0 = it1; it1 = it2;
        }
        if (lane == 0) {
            if (NSTAT > 1) atomicAdd(&g_ctr_item, (unsigned)(NSTAT - 1));
            TS(3);
        }
        return;
    }
    if (warp == 1) {
        if (lane == 0) {
            asm volatile("prefetch.tensormap [%0];" ::"l"(&tm_o) : "memory");
            asm volatile("prefetch.tensormap [%0];" ::"l"(&tm_gate) : "memory");
            asm volatile("prefetch.tensormap [%0];" ::"l"(&tm_up) : "memory");
            asm volatile("prefetch.tensormap [%0];" ::"l"(&tm_dn) : "memory");
        }
        const bool fo = cta < NOP && lane == 0, ff = cta < NFF && lane == 0;
        auto issue_wo = [&]() {
            if (fo) {
                mbar_expect_tx(bar_wo, 32 * WROW);
                const int r0 = (cta >> 2) * DH + (cta & 3) * 16;
                tensor_load_3d(sb + OFF_WO, &tm_o, r0, bar_wo, pol);
                tensor_load_3d(sb + OFF_WO + 16 * WROW, &tm_o, r0 + 64, bar_wo, pol);
            }
        };
        auto issue_gu = [&](int pc) {
            if (ff) {
                const int sl = (pc < NS) ? (s_misc[1] + pc) % NS : pc;
                const uint32_t dst = sb + OFF_RING + sl * SLOT;
                s_misc[2 + pc] = (int)dst;
                mbar_expect_tx(bar_gu + pc * 8, 2 * GU_BOX_BYTES);
                tensor_load_2d(dst, &tm_gate, cta * FC, pc * GU_PIECE_ROWS, bar_gu + pc * 8);
                tensor_load_2d(dst + GU_BOX_BYTES, &tm_up, cta * FC, pc * GU_PIECE_ROWS, bar_gu + pc * 8);
            }
        };
        auto issue_dn = [&]() { if (ff) { mbar_expect_tx(bar_dn, FC * WROW); tensor_load_3d(sb + OFF_DN, &tm_dn, cta * FC, bar_dn, pol); } };
        auto wait_free = [&](int k) { if (k < NS) asm volatile("bar.sync %0, 64;" ::"r"(BAR_FREE + k) : "memory"); };
        auto wait_wo = [&]() { if (cta < NOP) mbar_wait(bar_wo, 0); };
        auto wait_gu = [&](int pc) { if (cta < NFF) mbar_wait(bar_gu + pc * 8, 0); };
        wait_free(0); if (NS > 2) wait_free(1); if (NS > 3) wait_free(2);
        issue_wo(); wait_free(NS - 1); issue_gu(0); wait_wo(); issue_gu(1); wait_gu(0); issue_gu(2); wait_gu(1); issue_dn();
        if (lane == 0) TS(4);
        return;
    }

    const int vw = warp - 2, wt = tid - 64;
    if (cta >= NOP) { bar_sync<BAR_GO, 288>(); return; }
    if (vw >= 4) {
        const int w2 = vw - 4;
#pragma unroll
        for (int j = 0; j < 5; j++) if (j < 4 || lane < 16) reinterpret_cast<float4*>(s_x + w2 * DM)[lane + 32 * j] = xv[j];
        layernorm_store(xv, lane, smem + OFF_XN + w2 * WPITCH);
        bar_sync<BAR_Q, 128>();
        if (wt == 128) TS(23);
        if (w2 < 2) {
            mbar_wait(bar_wq, 0);
            if (wt == 128) TS(24);
            float c[2][4] = {{0.f, 0.f, 0.f, 0.f}, {0.f, 0.f, 0.f, 0.f}};
            const uint32_t bbase = sb + OFF_XN + (rr & 3) * WPITCH + id * 16;
            const uint32_t abase = sb + OFF_WQ + ((id >> 1) * 8 + rr) * 64 + (((2 * w2 + (id & 1)) ^ (rr >> 1)) << 4);
#pragma unroll 2
            for (int k2 = 0; k2 < DM / 32; k2++) {
                uint32_t bf[4], a0[4], a1[4];
                ldsm4(bf, bbase + k2 * 64);
                ldsm4t(a0, abase + k2 * 2048);
                ldsm4t(a1, abase + k2 * 2048 + 1024);
                mma16816(c[0], a0, bf[0], bf[1]);
                mma16816(c[1], a1, bf[2], bf[3]);
            }
            const bool od = g & 1;
            const float v0 = c[0][0] + c[1][0], v1 = c[0][1] + c[1][1], v2 = c[0][2] + c[1][2], v3 = c[0][3] + c[1][3];
            const float r0 = __shfl_xor_sync(0xffffffffu, od ? v0 : v1, 4), r1 = __shfl_xor_sync(0xffffffffu, od ? v2 : v3, 4);
            if (t < 2) {
                uint2* q = g_q + ((2 * t + (g & 1)) * NH + (cta >> 2)) * (DH / 2) + (cta & 3) * 16 + w2 * 8 + (g >> 1);
                st_pkt8(q, od ? pack_bf16(r0, v1) : pack_bf16(v0, r0), tag);
                st_pkt8(q + 4, od ? pack_bf16(r1, v3) : pack_bf16(v2, r1), tag);
            }
            if (wt == 128) TS(26);
        }
    }
    float* s_comb = reinterpret_cast<float*>(smem + OFF_COMB);
    float* s_red = reinterpret_cast<float*>(smem + OFF_RED);
#pragma unroll 1
    for (uint32_t pass = 0; pass < 2; pass++) {
        uint32_t real;
        asm volatile("mov.u32 %0, %1;" : "=r"(real) : "r"(pass));
        const uint32_t otag = real ? tag : 0u;
        const bool lead = real && wt == 0;
        if (real) bar_sync<BAR_GO, 288>(); else bar_sync<BAR_W, 256>();
        if (lead) TS(8);

        {
            constexpr int PW = IPH / 2;
            constexpr int NML = IPH / 32, NOV = PW / 4;
            const int b = vw >> 1, half = vw & 1;
            const int base = (b * NH + (cta >> 2)) * IPH;
            uint4 pk[NML + NOV];
            {
                uint32_t need[NML + NOV];
#pragma unroll
                for (int i = 0; i < NML + NOV; i++) { pk[i] = make_uint4(0u, 0u, 0u, 0u); need[i] = real; }
                const uint4* pml = g_ml + base + lane;
                const uint4* pov = g_op + (size_t)(base + half * PW + id) * 32 + (cta & 3) * 8 + rr;
                uint32_t n = 0;
                while (true) {
#pragma unroll
                    for (int i = 0; i < NML; i++) ld_pkt_if(need[i], pk[i], pml + i * 32);
#pragma unroll
                    for (int i = 0; i < NOV; i++) ld_pkt_if(need[NML + i], pk[NML + i], pov + i * 128);
                    uint32_t any = 0;
#pragma unroll
                    for (int i = 0; i < NML + NOV; i++) { need[i] = ((i < NML ? pk[i].z : pk[i].w) != tag) ? need[i] : 0u; any |= need[i]; }
                    if (!__any_sync(0xffffffffu, any != 0)) break;
                    if (++n > (1u << 22)) __trap();
                }
            }
            float M = __uint_as_float(pk[0].x);
#pragma unroll
            for (int i = 1; i < NML; i++) M = fmaxf(M, __uint_as_float(pk[i].x));
            M = warp_max(M);
            float wgt[NML], L = 0.f;
#pragma unroll
            for (int i = 0; i < NML; i++) { wgt[i] = ex2((__uint_as_float(pk[i].x) - M) * 1.4426950408889634f); L += wgt[i] * __uint_as_float(pk[i].y); }
            float4 a = make_float4(0.f, 0.f, 0.f, 0.f);
#pragma unroll
            for (int i = 0; i < NOV; i++) {
                const int j = i * 4;
                const float wsel = half ? wgt[(PW + j) / 32] : wgt[j / 32];
                const float w = __shfl_sync(0xffffffffu, wsel, ((half * PW + j) & 31) + id);
                const float4 o4 = unpack_f4(pk[NML + i]);
                a.x = fmaf(w, o4.x, a.x); a.y = fmaf(w, o4.y, a.y); a.z = fmaf(w, o4.z, a.z); a.w = fmaf(w, o4.w, a.w);
            }
            L = warp_sum(L);
#pragma unroll
            for (int o = 8; o <= 16; o <<= 1) {
                a.x += __shfl_xor_sync(0xffffffffu, a.x, o); a.y += __shfl_xor_sync(0xffffffffu, a.y, o);
                a.z += __shfl_xor_sync(0xffffffffu, a.z, o); a.w += __shfl_xor_sync(0xffffffffu, a.w, o);
            }
            if (lane < 8) reinterpret_cast<float4*>(s_comb + vw * 32)[lane] = a;
            if (lane == 0) s_comb[256 + vw] = L;
            bar_sync<BAR_W, 256>();
            if (lead) TS(9);
            uint32_t bo[4];
            {
                const int bb = g & 3;
                const float inv = __fdividef(1.0f, s_comb[256 + 2 * bb]);
                const float4* c0 = reinterpret_cast<const float4*>(s_comb + (2 * bb) * 32) + 2 * t;
                const float4 u0 = c0[0], u1 = c0[1], v0 = c0[8], v1 = c0[9];
                bo[0] = pack_bf16((u0.x + v0.x) * inv, (u1.x + v1.x) * inv);
                bo[1] = pack_bf16((u0.y + v0.y) * inv, (u1.y + v1.y) * inv);
                bo[2] = pack_bf16((u0.z + v0.z) * inv, (u1.z + v1.z) * inv);
                bo[3] = pack_bf16((u0.w + v0.w) * inv, (u1.w + v1.w) * inv);
            }
            if (real) mbar_wait(bar_wo, 0);
            if (lead) TS(10);
            const uint32_t abase = sb + OFF_WO + ((id >> 1) * 8 + rr) * WROW + (vw >> 2) * 128;
            const int jc = (vw & 3) * 2 + (id & 1), xr = rr + (vw >> 2);
#pragma unroll
            for (int i = 0; i < 5; i++) {
                if (i < 4 || vw < 4) {
                    float c[4] = {0.f, 0.f, 0.f, 0.f};
                    uint32_t a0[4], a1[4];
                    const uint32_t ad = abase + i * 256 + ((jc ^ ((xr + 2 * i) & 7)) << 4);
                    ldsm4t(a0, ad);
                    ldsm4t(a1, ad + 16 * WROW);
                    mma16816(c, a0, bo[0], bo[1]);
                    mma16816(c, a1, bo[2], bo[3]);
                    send_tile(1u, g_p1 + cta * DM + (vw + 8 * i) * 16, c, g, t, otag);
                }
            }
            if (lead) TS(11);
        }
        if (cta >= NFF) continue;
        if (cta < NRED) {
            reduce_cols<NOP>(real, g_p1 + cta * 8, s_red, vw, lane, tag);
            bar_sync<BAR_W, 256>();
            if (lead) TS(12);
            if (vw == 0) {
                float a = 0.f;
#pragma unroll
                for (int w = 0; w < 8; w++) a += s_red[w * 32 + rr * 4 + id];
                const float h = s_x[id * DM + cta * 8 + rr] + bfr(a);
                const uint32_t u = pack_bf16(h, __shfl_down_sync(0xffffffffu, h, 1));
                const uint32_t u2 = __shfl_down_sync(0xffffffffu, u, 2);
                st_pkt_if((rr & 3) == 0, g_h + id * (DM / 4) + cta * 2 + (rr >> 2), u, u2, otag, 0u);
            }
        }
        const int lw = vw - 4;
        if (lw >= 0) {
            uint4 hp[5];
            uint32_t want[5];
#pragma unroll
            for (int j = 0; j < 5; j++) want[j] = (j < 4 || lane < 16) ? real : 0u;
            poll_pkts<5, false>(hp, want, tag, [&](int j) { return g_h + lw * (DM / 4) + lane + 32 * j; });
            if (real && wt == 128) TS(13);
            float4 hv[5];
#pragma unroll
            for (int j = 0; j < 5; j++) {
                hv[j] = make_float4(bf_lo(hp[j].x), bf_hi(hp[j].x), bf_lo(hp[j].y), bf_hi(hp[j].y));
                if (want[j]) reinterpret_cast<float4*>(s_x + lw * DM)[lane + 32 * j] = hv[j];
            }
            layernorm_store(hv, lane, smem + OFF_XN + lw * WPITCH);
        }
        bar_sync<BAR_W, 256>();
        if (lead) TS(14);
        if (vw < FC / 8) {
            constexpr int KS = GU_PIECE_ROWS / 16;
            float c[2][4] = {{0.f, 0.f, 0.f, 0.f}, {0.f, 0.f, 0.f, 0.f}};
            const uint32_t bbase = sb + OFF_XN + (rr & 3) * WPITCH + id * 16;
            const uint32_t aoff = (id & 1) * GU_BOX_BYTES + ((id >> 1) * 8 + rr) * (FC * 2) + vw * 16;
#pragma unroll
            for (int pc = 0; pc < GU_PIECES; pc++) {
                if (real) mbar_wait(bar_gu + pc * 8, 0);
                const uint32_t ab = (uint32_t)s_misc[2 + pc] + aoff;
#pragma unroll
                for (int k2 = 0; k2 < KS / 2; k2++) {
                    uint32_t bf[4], a0[4], a1[4];
                    ldsm4(bf, bbase + (pc * KS + 2 * k2) * 32);
                    ldsm4t(a0, ab + (2 * k2) * 16 * FC * 2);
                    ldsm4t(a1, ab + (2 * k2 + 1) * 16 * FC * 2);
                    mma16816(c[0], a0, bf[0], bf[1]);
                    mma16816(c[1], a1, bf[2], bf[3]);
                }
            }
            if (lead) TS(15);
            if (t < 2) {
                __nv_bfloat16* s_act = reinterpret_cast<__nv_bfloat16*>(smem + OFF_ACT);
#pragma unroll
                for (int e = 0; e < 2; e++) {
                    const float gg = bfr(c[0][e] + c[1][e]), uu = bfr(c[0][2 + e] + c[1][2 + e]);
                    const float inner = 0.7978845608028654f * (gg + 0.044715f * gg * gg * gg);
                    const float th = 1.0f - __fdividef(2.0f, ex2(inner * 2.8853900817779268f) + 1.0f);
                    const float ge = bfr(0.5f * gg * (1.0f + th));
                    s_act[(2 * t + e) * (ACT_PITCH / 2) + vw * 8 + g] = __float2bfloat16_rn(ge * uu);
                }
            }
        }
        bar_sync<BAR_W, 256>();
        if (lead) TS(16);
        {
            uint32_t ba[6];
            const uint32_t* s_act32 = reinterpret_cast<const uint32_t*>(smem + OFF_ACT + (g & 3) * ACT_PITCH);
#pragma unroll
            for (int k = 0; k < 6; k++) ba[k] = s_act32[k * 4 + t];
            const uint32_t abase = sb + OFF_DN + ((id >> 1) * 8 + rr) * WROW + (vw >> 2) * 128;
            const uint32_t a2off = (id >> 1) ? 0u : 32u * WROW;
            const int jc = (vw & 3) * 2 + (id & 1), xr = rr + (vw >> 2);
            if (real) mbar_wait(bar_dn, 0);
            if (lead) TS(17);
#pragma unroll
            for (int i = 0; i < 5; i++) {
                if (i < 4 || vw < 4) {
                    float c[4] = {0.f, 0.f, 0.f, 0.f};
                    uint32_t a0[4], a1[4], a2[4];
                    const uint32_t ad = abase + i * 256 + ((jc ^ ((xr + 2 * i) & 7)) << 4);
                    ldsm4t(a0, ad);
                    ldsm4t(a1, ad + 16 * WROW);
                    ldsm4t(a2, ad + a2off);
                    mma16816(c, a0, ba[0], ba[1]);
                    mma16816(c, a1, ba[2], ba[3]);
                    mma16816(c, a2, ba[4], ba[5]);
                    send_tile(1u, g_p2 + cta * DM + (vw + 8 * i) * 16, c, g, t, otag);
                }
            }
            if (lead) TS(18);
        }
        if (cta < NRED) {
            reduce_cols<NFF>(real, g_p2 + cta * 8, s_red, vw, lane, tag);
            bar_sync<BAR_W, 256>();
            if (lead) TS(19);
            if (vw == 0) {
                float a = 0.f;
#pragma unroll
                for (int w = 0; w < 8; w++) a += s_red[w * 32 + rr * 4 + id];
                const float o = s_x[id * DM + cta * 8 + rr] + bfr(a);
                const uint32_t u = pack_bf16(o, __shfl_down_sync(0xffffffffu, o, 1));
                if (real && !(rr & 1)) *reinterpret_cast<uint32_t*>(p.out + id * DM + cta * 8 + rr) = u;
                if (lead) TS(20);
            }
        }
    }
}

typedef CUresult (*EncodeTiledFn)(CUtensorMap*, CUtensorMapDataType, cuuint32_t, void*, const cuuint64_t*, const cuuint64_t*,
                                  const cuuint32_t*, const cuuint32_t*, CUtensorMapInterleave, CUtensorMapSwizzle,
                                  CUtensorMapL2promotion, CUtensorMapFloatOOBfill);

}

extern "C" void kernel_launch(void* const* d_in, const int* in_sizes, int n_in, void* d_out, int out_size) {
    (void)in_sizes; (void)n_in; (void)out_size;
    static EncodeTiledFn encode = nullptr;
    if (!encode) {
        void* fn = nullptr;
        cudaDriverEntryPointQueryResult qr;
        cudaGetDriverEntryPoint("cuTensorMapEncodeTiled", &fn, cudaEnableDefault, &qr);
        encode = (EncodeTiledFn)fn;
        cudaFuncSetAttribute(fused_decode_kernel, cudaFuncAttributeMaxDynamicSharedMemorySize, SMEM_BYTES);
    }
    CUtensorMap tmq, tmo, tmg, tmu, tmd;
    const cuuint32_t estr[3] = {1, 1, 1};
    {
        const cuuint64_t gdim[2] = {(cuuint64_t)(NH * DH), (cuuint64_t)DM};
        const cuuint64_t gstr[1] = {(cuuint64_t)(NH * DH) * 2};
        const cuuint32_t box[2] = {32, 192};
        encode(&tmq, CU_TENSOR_MAP_DATA_TYPE_BFLOAT16, 2, d_in[3], gdim, gstr, box, estr, CU_TENSOR_MAP_INTERLEAVE_NONE,
               CU_TENSOR_MAP_SWIZZLE_64B, CU_TENSOR_MAP_L2_PROMOTION_L2_256B, CU_TENSOR_MAP_FLOAT_OOB_FILL_NONE);
    }
    {
        const cuuint64_t gdim[2] = {(cuuint64_t)DF, (cuuint64_t)DM};
        const cuuint64_t gstr[1] = {(cuuint64_t)DF * 2};
        const cuuint32_t box[2] = {(cuuint32_t)FC, (cuuint32_t)GU_PIECE_ROWS};
        encode(&tmg, CU_TENSOR_MAP_DATA_TYPE_BFLOAT16, 2, d_in[6], gdim, gstr, box, estr, CU_TENSOR_MAP_INTERLEAVE_NONE,
               CU_TENSOR_MAP_SWIZZLE_NONE, CU_TENSOR_MAP_L2_PROMOTION_L2_256B, CU_TENSOR_MAP_FLOAT_OOB_FILL_NONE);
        encode(&tmu, CU_TENSOR_MAP_DATA_TYPE_BFLOAT16, 2, d_in[7], gdim, gstr, box, estr, CU_TENSOR_MAP_INTERLEAVE_NONE,
               CU_TENSOR_MAP_SWIZZLE_NONE, CU_TENSOR_MAP_L2_PROMOTION_L2_256B, CU_TENSOR_MAP_FLOAT_OOB_FILL_NONE);
    }
    {
        const cuuint64_t gstr[2] = {128, (cuuint64_t)WROW};
        const cuuint64_t gdo[3] = {64, 9, (cuuint64_t)(NH * DH)}, gdd[3] = {64, 9, (cuuint64_t)DF};
        const cuuint32_t boxo[3] = {64, 9, 16}, boxd[3] = {64, 9, (cuuint32_t)FC};
        encode(&tmo, CU_TENSOR_MAP_DATA_TYPE_BFLOAT16, 3, d_in[4], gdo, gstr, boxo, estr, CU_TENSOR_MAP_INTERLEAVE_NONE,
               CU_TENSOR_MAP_SWIZZLE_128B, CU_TENSOR_MAP_L2_PROMOTION_L2_128B, CU_TENSOR_MAP_FLOAT_OOB_FILL_NONE);
        encode(&tmd, CU_TENSOR_MAP_DATA_TYPE_BFLOAT16, 3, d_in[8], gdd, gstr, boxd, estr, CU_TENSOR_MAP_INTERLEAVE_NONE,
               CU_TENSOR_MAP_SWIZZLE_128B, CU_TENSOR_MAP_L2_PROMOTION_L2_128B, CU_TENSOR_MAP_FLOAT_OOB_FILL_NONE);
    }
    Params p;
    p.x = (const __nv_bfloat16*)d_in[0];
    p.k = (const char*)d_in[1];
    p.v = (const char*)d_in[2];
    p.out = (__nv_bfloat16*)d_out;
    fused_decode_kernel<<<GRID, NTHR, SMEM_BYTES, cudaStreamPerThread>>>(p, tmq, tmo, tmg, tmu, tmd);
}
```

```cpp
#include <cuda_runtime.h>
#include <cuda_bf16.h>
#include <cuda.h>
#include <stdint.h>

namespace {

constexpr int NB = 4, DM = 576, NH = 32, SK = 8192, DH = 128, DF = 4608;
#define K_SLOTS 4
#define K_WIN 2
#define K_NPRE 36
#define K_HREP 4
#define K_STAGE 2
#define K_QEARLY 128
#define K_QWAIT 1
#define K_START 1
constexpr int KEYS   = 128;
constexpr int IPH    = SK / KEYS;
constexpr int NITEMS = NB * NH * IPH;
constexpr int NS     = K_SLOTS;
constexpr int NSTAT  = (NS + 1) / 2;
constexpr int SLOT   = KEYS * DH * 2;
constexpr int MT     = KEYS / 16;
constexpr int NTHR   = 320;
constexpr int GRID   = 132;
constexpr int NOP    = 128;
constexpr int FC     = 40;
constexpr int NFF    = (DF + FC - 1) / FC;
constexpr int NRED   = DM / 8;
constexpr int HREP   = K_HREP;
constexpr int WPITCH = DM * 2 + 16;
constexpr int GU_PIECE_ROWS = 192;
constexpr int GU_PIECES = DM / GU_PIECE_ROWS;
constexpr int GU_BOX_BYTES = GU_PIECE_ROWS * FC * 2;
constexpr int NSA    = NS < GU_PIECES ? GU_PIECES : NS;
static_assert(2 * GU_BOX_BYTES <= SLOT, "piece must fit a slot");

constexpr int WROW     = DM * 2;
constexpr int OFF_RING = 0;
constexpr int OFF_WO   = OFF_RING + NSA * SLOT;
constexpr int OFF_DN   = OFF_WO + 32 * WROW;
constexpr int OFF_XN   = OFF_DN + FC * WROW;
constexpr int OFF_X    = OFF_XN + 4 * WPITCH;
constexpr int OFF_COMB = OFF_X + NB * DM * 4;
constexpr int OFF_RED  = OFF_COMB + 8 * 32 * 4 + 32;
constexpr int OFF_ACT  = OFF_RED + 8 * 32 * 4;
constexpr int ACT_PITCH = 112;
constexpr int OFF_BAR  = OFF_ACT + 4 * ACT_PITCH;
constexpr int NBOX     = 11;
constexpr int NBARS    = NS + 1 + NBOX;
constexpr int OFF_MISC = OFF_BAR + NBARS * 8;
constexpr int SMEM_BYTES = OFF_MISC + 64;
constexpr int OFF_WQ   = OFF_WO;
static_assert(OFF_WO % 1024 == 0 && OFF_DN % 1024 == 0 && DM * 64 <= 32 * WROW, "staging");
static_assert(OFF_BAR % 8 == 0 && OFF_COMB % 16 == 0 && OFF_RED % 16 == 0, "align");
static_assert(SMEM_BYTES <= 232448, "smem");

__device__ unsigned int g_ctr_item;
__device__ __align__(128) uint2 g_q[NB * NH * DH / 2];
__device__ __align__(128) uint4 g_ml[NITEMS];
__device__ __align__(128) uint4 g_op[NITEMS * 32];
__device__ __align__(128) uint4 g_p1[NOP * DM];
__device__ __align__(128) uint4 g_h[HREP * NB * DM / 4];
__device__ __align__(128) uint4 g_p2[NFF * DM];

#define TS(i) do {} while (0)

__device__ __forceinline__ uint32_t smem_u32(const void* p) { return (uint32_t)__cvta_generic_to_shared(p); }
__device__ __forceinline__ void mbar_init(uint32_t bar, uint32_t cnt) { asm volatile("mbarrier.init.shared::cta.b64 [%0], %1;" ::"r"(bar), "r"(cnt) : "memory"); }
__device__ __forceinline__ void mbar_expect_tx(uint32_t bar, uint32_t bytes) { asm volatile("mbarrier.arrive.expect_tx.shared::cta.b64 _, [%0], %1;" ::"r"(bar), "r"(bytes) : "memory"); }
__device__ __forceinline__ bool mbar_try(uint32_t bar, uint32_t parity) {
    uint32_t ok;
    asm volatile("{\n.reg .pred p;\nmbarrier.try_wait.parity.shared::cta.b64 p, [%1], %2;\nselp.u32 %0, 1, 0, p;\n}" : "=r"(ok) : "r"(bar), "r"(parity) : "memory");
    return ok != 0;
}
__device__ __forceinline__ void mbar_wait(uint32_t bar, uint32_t parity) {
    uint32_t n = 0;
    while (!mbar_try(bar, parity)) { if (++n > (1u << 24)) __trap(); }
}
__device__ __forceinline__ void bulk_load(uint32_t dst, const void* src, uint32_t bytes, uint32_t bar, uint64_t pol) {
    asm volatile("cp.async.bulk.shared::cluster.global.mbarrier::complete_tx::bytes.L2::cache_hint [%0], [%1], %2, [%3], %4;"
                 ::"r"(dst), "l"(src), "r"(bytes), "r"(bar), "l"(pol) : "memory");
}
__device__ __forceinline__ void tensor_load_2d(uint32_t dst, const CUtensorMap* tm, int c0, int c1, uint32_t bar) {
    asm volatile("cp.async.bulk.tensor.2d.shared::cluster.global.mbarrier::complete_tx::bytes [%0], [%1, {%3, %4}], [%2];"
                 ::"r"(dst), "l"(tm), "r"(bar), "r"(c0), "r"(c1) : "memory");
}
__device__ __forceinline__ void tensor_load_3d(uint32_t dst, const CUtensorMap* tm, int row, uint32_t bar, uint64_t pol) {
    asm volatile("cp.async.bulk.tensor.3d.shared::cluster.global.mbarrier::complete_tx::bytes.L2::cache_hint [%0], [%1, {%3, %3, %4}], [%2], %5;"
                 ::"r"(dst), "l"(tm), "r"(bar), "r"(0), "r"(row), "l"(pol) : "memory");
}
__device__ __forceinline__ void ldsm4(uint32_t (&r)[4], uint32_t addr) {
    asm volatile("ldmatrix.sync.aligned.m8n8.x4.shared.b16 {%0,%1,%2,%3}, [%4];" : "=r"(r[0]), "=r"(r[1]), "=r"(r[2]), "=r"(r[3]) : "r"(addr) : "memory");
}
__device__ __forceinline__ void ldsm4t(uint32_t (&r)[4], uint32_t addr) {
    asm volatile("ldmatrix.sync.aligned.m8n8.x4.trans.shared.b16 {%0,%1,%2,%3}, [%4];" : "=r"(r[0]), "=r"(r[1]), "=r"(r[2]), "=r"(r[3]) : "r"(addr) : "memory");
}
__device__ __forceinline__ void mma16816(float (&c)[4], const uint32_t (&a)[4], uint32_t b0, uint32_t b1) {
    asm volatile("mma.sync.aligned.m16n8k16.row.col.f32.bf16.bf16.f32 {%0,%1,%2,%3}, {%4,%5,%6,%7}, {%8,%9}, {%0,%1,%2,%3};"
                 : "+f"(c[0]), "+f"(c[1]), "+f"(c[2]), "+f"(c[3]) : "r"(a[0]), "r"(a[1]), "r"(a[2]), "r"(a[3]), "r"(b0), "r"(b1));
}
__device__ __forceinline__ void mma1688(float (&c)[4], uint32_t a0, uint32_t a1, uint32_t b0) {
    asm volatile("mma.sync.aligned.m16n8k8.row.col.f32.bf16.bf16.f32 {%0,%1,%2,%3}, {%4,%5}, {%6}, {%0,%1,%2,%3};"
                 : "+f"(c[0]), "+f"(c[1]), "+f"(c[2]), "+f"(c[3]) : "r"(a0), "r"(a1), "r"(b0));
}
__device__ __forceinline__ float bfr(float x) { return __bfloat162float(__float2bfloat16_rn(x)); }
__device__ __forceinline__ uint32_t pack_bf16(float lo, float hi) {
    uint32_t r; asm("cvt.rn.bf16x2.f32 %0, %1, %2;" : "=r"(r) : "f"(hi), "f"(lo)); return r;
}
__device__ __forceinline__ float bf_lo(uint32_t u) { return __uint_as_float(u << 16); }
__device__ __forceinline__ float bf_hi(uint32_t u) { return __uint_as_float(u & 0xffff0000u); }
__device__ __forceinline__ float ex2(float x) { float r; asm("ex2.approx.ftz.f32 %0, %1;" : "=f"(r) : "f"(x)); return r; }
__device__ __forceinline__ void st_pkt_if(uint32_t on, void* p, uint32_t a, uint32_t b, uint32_t c, uint32_t d) {
    asm volatile("{\n.reg .pred p;\n.reg .b64 l, h;\n.reg .b128 v;\nsetp.ne.u32 p, %5, 0;\nmov.b64 l, {%1,%2};\nmov.b64 h, {%3,%4};\nmov.b128 v, {l,h};\n"
                 "@p st.relaxed.gpu.global.b128 [%0], v;\n}" ::"l"(p), "r"(a), "r"(b), "r"(c), "r"(d), "r"(on) : "memory");
}
__device__ __forceinline__ void ld_pkt_if(uint32_t on, uint4& v, const void* p) {
    asm volatile("{\n.reg .pred p;\n.reg .b64 l, h;\n.reg .b128 v;\nsetp.ne.u32 p, %5, 0;\nmov.b64 l, {%0,%1};\nmov.b64 h, {%2,%3};\nmov.b128 v, {l,h};\n"
                 "@p ld.relaxed.gpu.global.b128 v, [%4];\nmov.b128 {l,h}, v;\nmov.b64 {%0,%1}, l;\nmov.b64 {%2,%3}, h;\n}"
                 : "+r"(v.x), "+r"(v.y), "+r"(v.z), "+r"(v.w) : "l"(p), "r"(on) : "memory");
}
__device__ __forceinline__ void st_pkt8(void* p, uint32_t a, uint32_t b) {
    asm volatile("{\n.reg .b64 v;\nmov.b64 v, {%1,%2};\nst.relaxed.gpu.global.b64 [%0], v;\n}" ::"l"(p), "r"(a), "r"(b) : "memory");
}
__device__ __forceinline__ uint2 ld_pkt8(const void* p) {
    uint2 v;
    asm volatile("{\n.reg .b64 v;\nld.relaxed.gpu.global.b64 v, [%2];\nmov.b64 {%0,%1}, v;\n}" : "=r"(v.x), "=r"(v.y) : "l"(p) : "memory");
    return v;
}
__device__ __forceinline__ void st_f4_if(uint32_t on, void* p, float a, float b, float c, float d, uint32_t tag) {
    const uint32_t ud = __float_as_uint(d);
    st_pkt_if(on, p, __byte_perm(__float_as_uint(a), ud, 0x3217), __byte_perm(__float_as_uint(b), ud, 0x3216),
              __byte_perm(__float_as_uint(c), ud, 0x3215), tag);
}
__device__ __forceinline__ float4 unpack_f4(const uint4& v) {
    const uint32_t d = __byte_perm(__byte_perm(v.z, v.y, 0x0400), v.x, 0x4210);
    return make_float4(__uint_as_float(v.x & 0xffffff00u), __uint_as_float(v.y & 0xffffff00u), __uint_as_float(v.z & 0xffffff00u), __uint_as_float(d & 0xffffff00u));
}
template <int N, bool W, class AddrFn>
__device__ __forceinline__ void poll_pkts(uint4 (&v)[N], const uint32_t (&want)[N], uint32_t tag, AddrFn addr) {
    uint32_t need[N];
#pragma unroll
    for (int i = 0; i < N; i++) { v[i] = make_uint4(0u, 0u, 0u, 0u); need[i] = want[i]; }
    uint32_t n = 0;
    while (true) {
#pragma unroll
        for (int i = 0; i < N; i++) ld_pkt_if(need[i], v[i], addr(i));
        uint32_t any = 0;
#pragma unroll
        for (int i = 0; i < N; i++) { need[i] = ((W ? v[i].w : v[i].z) != tag) ? need[i] : 0u; any |= need[i]; }
        if (!__any_sync(0xffffffffu, any != 0)) break;
        if (++n > (1u << 22)) __trap();
    }
}
template <int ID, int N> __device__ __forceinline__ void bar_sync() { asm volatile("bar.sync %0, %1;" ::"n"(ID), "n"(N) : "memory"); }
template <int ID, int N> __device__ __forceinline__ void bar_arrive() { asm volatile("bar.arrive %0, %1;" ::"n"(ID), "n"(N) : "memory"); }
constexpr int BAR_W = 1;
constexpr int BAR_GO = 2;
constexpr int BAR_FREE = 3;
constexpr int BAR_Q = 8;
constexpr int BAR_C = 11;
constexpr int BAR_ST = 12;
constexpr int BAR_XN = 9;
constexpr int BAR_ACT = 10;
__device__ __forceinline__ float warp_sum(float v) {
#pragma unroll
    for (int o = 16; o > 0; o >>= 1) v += __shfl_xor_sync(0xffffffffu, v, o);
    return v;
}
__device__ __forceinline__ float warp_max(float v) {
#pragma unroll
    for (int o = 16; o > 0; o >>= 1) v = fmaxf(v, __shfl_xor_sync(0xffffffffu, v, o));
    return v;
}
__device__ __forceinline__ float2 ln_stats(const float4 (&v)[5], int lane) {
    const float piv = __shfl_sync(0xffffffffu, v[0].x, 0);
    float s = 0.f, ss = 0.f;
#pragma unroll
    for (int j = 0; j < 5; j++) {
        const float a = v[j].x - piv, b = v[j].y - piv, c = v[j].z - piv, d = v[j].w - piv;
        if (j < 4 || lane < 16) { s += (a + b) + (c + d); ss += (a * a + b * b) + (c * c + d * d); }
    }
#pragma unroll
    for (int o = 16; o > 0; o >>= 1) { s += __shfl_xor_sync(0xffffffffu, s, o); ss += __shfl_xor_sync(0xffffffffu, ss, o); }
    const float dm = s * (1.0f / DM);
    const float var = bfr(fmaxf(ss * (1.0f / DM) - dm * dm, 0.f));
    float sd, rs;
    asm("sqrt.approx.f32 %0, %1;" : "=f"(sd) : "f"(bfr(var + 1e-5f)));
    asm("rcp.approx.f32 %0, %1;" : "=f"(rs) : "f"(bfr(sd)));
    return make_float2(bfr(piv + dm), rs);
}
__device__ __forceinline__ void send_tile(uint4* dst, const float (&c)[4], int g, int t, uint32_t tag) {
    st_f4_if(t < 2, dst + g + 8 * t, c[0], c[1], c[2], c[3], tag);
}
template <int NSRC>
__device__ __forceinline__ void reduce_cols(uint32_t on, const uint4* src, float* s_red, int vw, int lane, uint32_t tag) {
    uint4 v[4];
    uint32_t want[4];
    const int c0 = vw * 4 + (lane >> 3);
#pragma unroll
    for (int i = 0; i < 4; i++) want[i] = (c0 + 32 * i < NSRC) ? on : 0u;
    poll_pkts<4, true>(v, want, tag, [&](int i) { return src + (c0 + 32 * i) * DM + (lane & 7); });
    float4 a = make_float4(0.f, 0.f, 0.f, 0.f);
#pragma unroll
    for (int i = 0; i < 4; i++) { const float4 f = unpack_f4(v[i]); a.x += f.x; a.y += f.y; a.z += f.z; a.w += f.w; }
#pragma unroll
    for (int o = 8; o <= 16; o <<= 1) {
        a.x += __shfl_xor_sync(0xffffffffu, a.x, o); a.y += __shfl_xor_sync(0xffffffffu, a.y, o);
        a.z += __shfl_xor_sync(0xffffffffu, a.z, o); a.w += __shfl_xor_sync(0xffffffffu, a.w, o);
    }
    if (lane < 8) reinterpret_cast<float4*>(s_red + vw * 32)[lane] = a;
}

struct Params {
    const __nv_bfloat16* x;
    const char* k;
    const char* v;
    __nv_bfloat16* out;
};

__global__ void __launch_bounds__(NTHR, 1)
fused_decode_kernel(const Params p, const __grid_constant__ CUtensorMap tm_q, const __grid_constant__ CUtensorMap tm_o,
                    const __grid_constant__ CUtensorMap tm_gate, const __grid_constant__ CUtensorMap tm_up,
                    const __grid_constant__ CUtensorMap tm_dn) {
    extern __shared__ __align__(1024) uint8_t smem[];
    const uint32_t sb = smem_u32(smem);
    const int tid = threadIdx.x, warp = tid >> 5, lane = tid & 31, cta = blockIdx.x;
    const int g = lane >> 2, t = lane & 3, id = lane >> 3, rr = lane & 7;
    const uint32_t bar_ring = sb + OFF_BAR, bar_wq = bar_ring + NS * 8, bar_box = bar_wq + 8;
    volatile int* s_misc = reinterpret_cast<volatile int*>(smem + OFF_MISC);
    float* s_x = reinterpret_cast<float*>(smem + OFF_X);
    uint64_t pol;
    asm volatile("createpolicy.fractional.L2::evict_first.b64 %0, 1.0;" : "=l"(pol));

    auto first_tile = [&](int n) {
        mbar_expect_tx(bar_ring + n * 8, SLOT);
        bulk_load(sb + OFF_RING + n * SLOT, ((n & 1) ? p.v : p.k) + (size_t)((n >> 1) * GRID + cta) * SLOT, SLOT, bar_ring + n * 8, pol);
    };
    auto load_wq = [&]() {
        mbar_expect_tx(bar_wq, DM * 64);
#pragma unroll
        for (int i = 0; i < 3; i++) tensor_load_2d(sb + OFF_WQ + i * 192 * 64, &tm_q, cta * 32, i * 192, bar_wq);
    };
    if (tid == 0) {
        TS(0);
#pragma unroll
        for (int i = 0; i <= NS; i++) mbar_init(bar_ring + i * 8, 1);
        asm volatile("fence.mbarrier_init.release.cluster;" ::: "memory");
        asm volatile("fence.proxy.async.shared::cta;" ::: "memory");
        TS(28);
        if (cta < K_QEARLY) load_wq();
        first_tile(0);
        if (!(K_STAGE & 1) || cta >= NOP) first_tile(1);
        if (!(K_STAGE & 2)) for (int n = 2; n < NS; n++) first_tile(n);
        TS(29);
    }
    if (warp >= 6) {
        uint2 u[5];
#pragma unroll
        for (int j = 0; j < 5; j++) if (j < 4 || lane < 16) u[j] = __ldg(reinterpret_cast<const uint2*>(p.x + (warp - 6) * DM) + lane + 32 * j);
#pragma unroll
        for (int j = 0; j < 5; j++) if (j < 4 || lane < 16)
            reinterpret_cast<float4*>(s_x + (warp - 6) * DM)[lane + 32 * j] = make_float4(bf_lo(u[j].x), bf_hi(u[j].x), bf_lo(u[j].y), bf_hi(u[j].y));
    } else if (warp == 1) {
        if (lane == 0) {
            unsigned int c;
            asm volatile("ld.relaxed.gpu.global.u32 %0, [%1];" : "=r"(c) : "l"(&g_ctr_item) : "memory");
            s_misc[0] = (int)(c / NITEMS + 1);
        } else if (lane <= NBOX) {
            mbar_init(bar_wq + lane * 8, 1);
            asm volatile("fence.mbarrier_init.release.cluster;" ::: "memory");
            s_misc[lane] = (int)sb;
        }
    }
    __syncthreads();
    const uint32_t tag = (uint32_t)s_misc[0];

    if (warp == 0) {
        uint32_t offK[4], offV[4];
#pragma unroll
        for (int j = 0; j < 4; j++) {
            offK[j] = sb + OFF_RING + ((id & 1) * 8 + rr) * 256 + (((2 * j + (id >> 1)) ^ rr) << 4);
            offV[j] = sb + OFF_RING + ((id >> 1) * 8 + rr) * 256 + (((2 * j + (id & 1)) ^ rr) << 4);
        }
        const bool valid = (t == (g >> 1));
        const int odd = g & 1;
        const float SCALE = 0.08838834764831845f, LOG2E = 1.4426950408889634f;
        uint32_t it0 = cta, it1 = (NSTAT > 1) ? GRID + cta : 0u, it2 = 0u;
        uint32_t slot = 0, ph = 0, nfree = 0;
        auto claim = [&]() -> uint32_t { uint32_t v = 0; if (lane == 0) v = (atomicAdd(&g_ctr_item, 1u) % NITEMS) + NSTAT * GRID; return v; };
        auto load_q = [&](uint2 (&qq)[16], uint32_t item) {
            const uint2* qp = g_q + (min(item, (uint32_t)NITEMS - 1) / IPH) * (DH / 2) + t;
#pragma unroll
            for (int c = 0; c < 16; c++) qq[c] = ld_pkt8(qp + ((c ^ g) << 2));
        };
        auto refill = [&](const char* base, uint32_t item) {
            if (item < (uint32_t)NITEMS) {
                if (lane == 0) { mbar_expect_tx(bar_ring + slot * 8, SLOT); bulk_load(sb + OFF_RING + slot * SLOT, base + (size_t)item * SLOT, SLOT, bar_ring + slot * 8, pol); }
            } else {
                if (nfree == 0) { if (lane == 0) { s_misc[1] = (int)slot; TS(2); } bar_arrive<BAR_GO, 288>(); }
                asm volatile("bar.arrive %0, 64;" ::"r"(BAR_FREE + nfree) : "memory");
                nfree++;
            }
            if (++slot == NS) { slot = 0; ph ^= 1; }
        };
        uint2 qn[16];
        uint32_t pend = 0;
        if (NS == 2) pend = claim();
        mbar_wait(bar_ring, 0);
        if (K_QEARLY < NOP && lane == 0 && cta >= K_QEARLY && cta < NOP) load_wq();
        if ((K_STAGE & 2) && lane == 0) for (int n = 2; n < NS; n++) first_tile(n);
        if (lane == 0) TS(30);
        load_q(qn, it0);
        while (true) {
            uint32_t qf[16];
            for (uint32_t n = 0;; n++) {
                uint32_t bad = 0;
#pragma unroll
                for (int c = 0; c < 16; c++) { qf[c] = qn[c].x; bad |= qn[c].y ^ tag; }
                if (!__any_sync(0xffffffffu, bad != 0)) break;
                if (n > (1u << 22)) __trap();
                load_q(qn, it0);
            }
            if (NS == 3) { if (it1 < (uint32_t)NITEMS) pend = claim(); load_q(qn, it1); }
            if (NS == 4) { load_q(qn, it1); }
            mbar_wait(bar_ring + slot * 8, ph);
            float sc[MT][4];
#pragma unroll
            for (int m = 0; m < MT; m++) { sc[m][0] = sc[m][1] = sc[m][2] = sc[m][3] = 0.f; }
            {
                const uint32_t so = slot * SLOT;
#pragma unroll
                for (int j = 0; j < 8; j++) {
#pragma unroll
                    for (int m = 0; m < MT; m++) {
                        uint32_t a[4];
                        ldsm4(a, offK[j & 3] + so + m * 4096 + (j >> 2) * 128);
                        mma16816(sc[m], a, qf[2 * j], qf[2 * j + 1]);
                    }
                }
            }
            if (NS == 2) { it1 = __shfl_sync(0xffffffffu, pend, 0); refill(p.k, it1); if (it1 < (uint32_t)NITEMS) pend = claim(); load_q(qn, it1); }
            if (NS == 3) { __syncwarp(); refill(p.v, it1); }
            if (NS == 4) {
                if (it0 < GRID) pend = claim();
                it2 = (it1 < (uint32_t)NITEMS) ? __shfl_sync(0xffffffffu, pend, 0) : (uint32_t)NITEMS;
                refill(p.k, it2);
            }
            float s[2 * MT];
            float mx = -INFINITY;
#pragma unroll
            for (int m = 0; m < MT; m++) {
                s[2 * m]     = bfr(bfr(odd ? sc[m][1] : sc[m][0]) * SCALE);
                s[2 * m + 1] = bfr(bfr(odd ? sc[m][3] : sc[m][2]) * SCALE);
                mx = fmaxf(mx, fmaxf(s[2 * m], s[2 * m + 1]));
            }
            mx = warp_max(valid ? mx : -INFINITY);
            const float mref = (mx == -INFINITY) ? 0.f : mx;
            float l = 0.f;
            uint32_t pb[2 * MT];
#pragma unroll
            for (int i = 0; i < 2 * MT; i++) {
                const float e = valid ? ex2((s[i] - mref) * LOG2E) : 0.f;
                l += e;
                pb[i] = pack_bf16(e, 0.f) << (odd * 16);
            }
            l = warp_sum(l);
            st_pkt_if(lane == 0, &g_ml[it0], __float_as_uint(mx), __float_as_uint(l), tag, 0u);
            float acc[8][4];
#pragma unroll
            for (int i = 0; i < 8; i++) { acc[i][0] = acc[i][1] = acc[i][2] = acc[i][3] = 0.f; }
            mbar_wait(bar_ring + slot * 8, ph);
            {
                const uint32_t so = slot * SLOT;
#pragma unroll
                for (int m = 0; m < MT; m++) {
#pragma unroll
                    for (int i = 0; i < 8; i++) {
                        uint32_t a[4];
                        ldsm4t(a, offV[i & 3] + so + m * 4096 + (i >> 2) * 128);
                        mma16816(acc[i], a, pb[2 * m], pb[2 * m + 1]);
                    }
                }
            }
            if (NS == 2) { __syncwarp(); refill(p.v, it1); }
            if (NS == 3) { it2 = (it1 < (uint32_t)NITEMS) ? __shfl_sync(0xffffffffu, pend, 0) : (uint32_t)NITEMS; if (nfree < NS) refill(p.k, it2); }
            if (NS == 4) { __syncwarp(); refill(p.v, it2); if (it2 < (uint32_t)NITEMS) pend = claim(); }
            float T[16];
#pragma unroll
            for (int i = 0; i < 8; i++) { T[2 * i] = acc[i][0] + acc[i][3]; T[2 * i + 1] = acc[i][2] + acc[i][1]; }
            float U[16];
#pragma unroll
            for (int c = 0; c < 16; c++) if (!(c & 2)) U[c] = T[c] + __shfl_xor_sync(0xffffffffu, T[c ^ 2], 1);
            const float y0 = U[0] + __shfl_xor_sync(0xffffffffu, U[4], 2), y1 = U[1] + __shfl_xor_sync(0xffffffffu, U[5], 2);
            const float y2 = U[8] + __shfl_xor_sync(0xffffffffu, U[12], 2), y3 = U[9] + __shfl_xor_sync(0xffffffffu, U[13], 2);
            st_f4_if(1u, g_op + (size_t)it0 * 32 + t * 8 + g, y0, y1, y2, y3, tag);
            if (it1 >= (uint32_t)NITEMS) break;
            it0 = it1; it1 = it2;
        }
        if (lane == 0) {
            if (NSTAT > 1) atomicAdd(&g_ctr_item, (unsigned)(NSTAT - 1));
            TS(3);
        }
        if (cta >= NFF) return;
    } else if (warp == 1) {
        if (lane == 0) {
            asm volatile("prefetch.tensormap [%0];" ::"l"(&tm_o) : "memory");
            asm volatile("prefetch.tensormap [%0];" ::"l"(&tm_gate) : "memory");
            asm volatile("prefetch.tensormap [%0];" ::"l"(&tm_up) : "memory");
            asm volatile("prefetch.tensormap [%0];" ::"l"(&tm_dn) : "memory");
        }
        constexpr int NSP = NSA - NS;
        const int nbox = cta < NFF ? NBOX : (cta < NOP ? 2 : 0);
        int waited = 0;
        auto wait_free = [&](int k) { for (; waited <= k && waited < NS; waited++) asm volatile("bar.sync %0, 64;" ::"r"(BAR_FREE + waited) : "memory"); };
        wait_free(K_START);
#pragma unroll
        for (int i = 0; i < NBOX; i++) {
            if (i < nbox) {
                const int pc = (i - 2) >> 1;
                if (i >= 2 && i < 8) wait_free(pc - NSP);
                if (i >= K_WIN) mbar_wait(bar_box + (i - K_WIN) * 8, 0);
                if (lane == 0) {
                    const uint32_t bar = bar_box + i * 8;
                    if (i < 2) {
                        mbar_expect_tx(bar, 16 * WROW);
                        const int r0 = (cta >> 2) * DH + (cta & 3) * 16 + i * 64;
                        tensor_load_3d(sb + OFF_WO + i * 16 * WROW, &tm_o, r0, bar, pol);
                        tensor_load_3d(sb + OFF_WO + (i * 16 + 8) * WROW, &tm_o, r0 + 8, bar, pol);
                    } else if (i < 8) {
                        const int sl = (pc < NSP) ? NS + pc : (s_misc[1] + pc - NSP) % NS;
                        const uint32_t dst = sb + OFF_RING + sl * SLOT;
                        s_misc[2 + pc] = (int)dst;
                        mbar_expect_tx(bar, GU_BOX_BYTES);
                        tensor_load_2d(dst + (i & 1) * GU_BOX_BYTES, (i & 1) ? &tm_up : &tm_gate, cta * FC, pc * GU_PIECE_ROWS, bar);
                    } else {
                        const int r0 = (i - 8) * 16;
                        mbar_expect_tx(bar, (i < 10 ? 16 : 8) * WROW);
                        tensor_load_3d(sb + OFF_DN + r0 * WROW, &tm_dn, cta * FC + r0, bar, pol);
                        if (i < 10) tensor_load_3d(sb + OFF_DN + (r0 + 8) * WROW, &tm_dn, cta * FC + r0 + 8, bar, pol);
                    }
                }
                __syncwarp();
            }
        }
        wait_free(NS - 1);
        return;
    }

    const int vw = (warp == 0) ? 8 : warp - 2, wt = tid - 64;
    if (cta >= NOP) { bar_sync<BAR_GO, 288>(); return; }
    if (vw >= 4 && vw < 8) {
        const int w2 = vw - 4;
        float4 xv[5];
#pragma unroll
        for (int j = 0; j < 5; j++) xv[j] = reinterpret_cast<const float4*>(s_x + w2 * DM)[(j < 4 || lane < 16) ? lane + 32 * j : lane];
        const float2 st = ln_stats(xv, lane);
#pragma unroll
        for (int j = 0; j < 5; j++) {
            uint2 o;
            o.x = pack_bf16(bfr(xv[j].x - st.x) * st.y, bfr(xv[j].y - st.x) * st.y);
            o.y = pack_bf16(bfr(xv[j].z - st.x) * st.y, bfr(xv[j].w - st.x) * st.y);
            if (j < 4 || lane < 16) *reinterpret_cast<uint2*>(smem + OFF_XN + w2 * WPITCH + (lane + 32 * j) * 8) = o;
        }
        bar_sync<BAR_Q, 128>();
        if (wt == 128) TS(23);
        if (w2 < 2) {
            mbar_wait(bar_wq, 0);
            if ((K_STAGE & 1) && wt == 128) first_tile(1);
            if (wt == 128) TS(24);
            float c[2][4] = {{0.f, 0.f, 0.f, 0.f}, {0.f, 0.f, 0.f, 0.f}};
            const uint32_t bbase = sb + OFF_XN + (rr & 3) * WPITCH + id * 16;
            const uint32_t abase = sb + OFF_WQ + ((id >> 1) * 8 + rr) * 64 + (((2 * w2 + (id & 1)) ^ (rr >> 1)) << 4);
#pragma unroll 2
            for (int k2 = 0; k2 < DM / 32; k2++) {
                uint32_t bf[4], a0[4], a1[4];
                ldsm4(bf, bbase + k2 * 64);
                ldsm4t(a0, abase + k2 * 2048);
                ldsm4t(a1, abase + k2 * 2048 + 1024);
                mma16816(c[0], a0, bf[0], bf[1]);
                mma16816(c[1], a1, bf[2], bf[3]);
            }
            const bool od = g & 1;
            const float v0 = c[0][0] + c[1][0], v1 = c[0][1] + c[1][1], v2 = c[0][2] + c[1][2], v3 = c[0][3] + c[1][3];
            const float r0 = __shfl_xor_sync(0xffffffffu, od ? v0 : v1, 4), r1 = __shfl_xor_sync(0xffffffffu, od ? v2 : v3, 4);
            if (t < 2) {
                uint2* q = g_q + ((2 * t + (g & 1)) * NH + (cta >> 2)) * (DH / 2) + (cta & 3) * 16 + w2 * 8 + (g >> 1);
                st_pkt8(q, od ? pack_bf16(r0, v1) : pack_bf16(v0, r0), tag);
                st_pkt8(q + 4, od ? pack_bf16(r1, v3) : pack_bf16(v2, r1), tag);
            }
            if (wt == 128) TS(26);
        }
    }
    float* s_comb = reinterpret_cast<float*>(smem + OFF_COMB);
    float* s_red = reinterpret_cast<float*>(smem + OFF_RED);
#pragma unroll 1
    for (uint32_t pass = (vw == 8) ? 1u : 0u; pass < 2; pass++) {
        uint32_t real;
        asm volatile("mov.u32 %0, %1;" : "=r"(real) : "r"(pass));
        const uint32_t otag = real ? tag : 0u;
        const bool lead = real && wt == 0;
        if (vw < 8) {
            if (real) bar_sync<BAR_GO, 288>(); else bar_sync<BAR_W, 256>();
            if (lead) TS(8);
            constexpr int PW = IPH / 2;
            constexpr int NML = IPH / 32, NOV = PW / 4;
            const int b = vw >> 1, half = vw & 1;
            const int base = (b * NH + (cta >> 2)) * IPH;
            uint4 pk[NML + NOV];
            {
                uint32_t need[NML + NOV];
#pragma unroll
                for (int i = 0; i < NML + NOV; i++) { pk[i] = make_uint4(0u, 0u, 0u, 0u); need[i] = real; }
                const uint4* pml = g_ml + base + lane;
                const uint4* pov = g_op + (size_t)(base + half * PW + id) * 32 + (cta & 3) * 8 + rr;
                uint32_t n = 0;
                while (true) {
#pragma unroll
                    for (int i = 0; i < NML; i++) ld_pkt_if(need[i], pk[i], pml + i * 32);
#pragma unroll
                    for (int i = 0; i < NOV; i++) ld_pkt_if(need[NML + i], pk[NML + i], pov + i * 128);
                    uint32_t any = 0;
#pragma unroll
                    for (int i = 0; i < NML + NOV; i++) { need[i] = ((i < NML ? pk[i].z : pk[i].w) != tag) ? need[i] : 0u; any |= need[i]; }
                    if (!__any_sync(0xffffffffu, any != 0)) break;
                    if (++n > (1u << 22)) __trap();
                }
            }
            if (real && wt == 224) TS(27);
            float M = __uint_as_float(pk[0].x);
#pragma unroll
            for (int i = 1; i < NML; i++) M = fmaxf(M, __uint_as_float(pk[i].x));
            M = warp_max(M);
            float wgt[NML], L = 0.f;
#pragma unroll
            for (int i = 0; i < NML; i++) { wgt[i] = ex2((__uint_as_float(pk[i].x) - M) * 1.4426950408889634f); L += wgt[i] * __uint_as_float(pk[i].y); }
            float4 a = make_float4(0.f, 0.f, 0.f, 0.f);
#pragma unroll
            for (int i = 0; i < NOV; i++) {
                const int j = i * 4;
                const float wsel = half ? wgt[(PW + j) / 32] : wgt[j / 32];
                const float w = __shfl_sync(0xffffffffu, wsel, ((half * PW + j) & 31) + id);
                const float4 o4 = unpack_f4(pk[NML + i]);
                a.x = fmaf(w, o4.x, a.x); a.y = fmaf(w, o4.y, a.y); a.z = fmaf(w, o4.z, a.z); a.w = fmaf(w, o4.w, a.w);
            }
            L = warp_sum(L);
#pragma unroll
            for (int o = 8; o <= 16; o <<= 1) {
                a.x += __shfl_xor_sync(0xffffffffu, a.x, o); a.y += __shfl_xor_sync(0xffffffffu, a.y, o);
                a.z += __shfl_xor_sync(0xffffffffu, a.z, o); a.w += __shfl_xor_sync(0xffffffffu, a.w, o);
            }
            const float inv = __fdividef(1.0f, L);
            if (lane < 8) reinterpret_cast<float4*>(s_comb + vw * 32)[lane] = make_float4(a.x * inv, a.y * inv, a.z * inv, a.w * inv);
            if (vw < 6) {
                uint32_t wa[6][2][4];
                if (real) { mbar_wait(bar_box, 0); mbar_wait(bar_box + 8, 0); }
#pragma unroll
                for (int i = 0; i < 6; i++) {
                    const int mt = vw + 6 * i;
                    const uint32_t ad = sb + OFF_WO + ((id >> 1) * 8 + rr) * WROW + (mt >> 2) * 128 + ((((mt & 3) * 2 + (id & 1)) ^ ((rr + (mt >> 2)) & 7)) << 4);
                    ldsm4t(wa[i][0], ad);
                    ldsm4t(wa[i][1], ad + 16 * WROW);
                }
                if (real) bar_sync<BAR_C, 256>();
                if (lead) TS(9);
                const float4* c0 = reinterpret_cast<const float4*>(s_comb + (g & 3) * 64) + 2 * t;
                const float4 u0 = c0[0], u1 = c0[1], v0 = c0[8], v1 = c0[9];
                const uint32_t bo0 = pack_bf16(u0.x + v0.x, u1.x + v1.x), bo1 = pack_bf16(u0.y + v0.y, u1.y + v1.y);
                const uint32_t bo2 = pack_bf16(u0.z + v0.z, u1.z + v1.z), bo3 = pack_bf16(u0.w + v0.w, u1.w + v1.w);
                float c[6][4];
#pragma unroll
                for (int i = 0; i < 6; i++) { c[i][0] = c[i][1] = c[i][2] = c[i][3] = 0.f; mma16816(c[i], wa[i][0], bo0, bo1); }
#pragma unroll
                for (int i = 0; i < 6; i++) mma16816(c[i], wa[i][1], bo2, bo3);
#pragma unroll
                for (int i = 0; i < 6; i++) send_tile(g_p1 + cta * DM + (vw + 6 * i) * 16, c[i], g, t, otag);
            } else {
                __syncwarp();
                if (real) bar_arrive<BAR_C, 256>();
            }
            if (lead) TS(11);
            if (cta >= NFF) continue;
            if (cta < NRED) {
                reduce_cols<NOP>(real, g_p1 + cta * 8, s_red, vw, lane, tag);
                if (real) bar_sync<BAR_W, 256>();
                if (lead) TS(12);
                if (vw == 0) {
                    const int ob = (cta & 1) * 2 + (lane >> 4), oc = (cta >> 1) * 16 + (lane & 15);
                    float a1 = 0.f;
#pragma unroll
                    for (int w = 0; w < 8; w++) a1 += s_red[w * 32 + rr * 4 + (id & 1) * 2 + (id >> 1)];
                    const float h = s_x[ob * DM + oc] + bfr(a1);
                    const uint32_t u = pack_bf16(h, __shfl_down_sync(0xffffffffu, h, 1));
                    const uint32_t u0 = __shfl_sync(0xffffffffu, u, lane & ~3), u2 = __shfl_sync(0xffffffffu, u, (lane & ~3) + 2);
                    st_pkt_if(t < HREP, g_h + (t * NB + ob) * (DM / 4) + (oc >> 2), u0, u2, otag, 0u);
                }
            }
        }
        if (vw < 4 || vw == 8) {
            const int ct = (vw == 8) ? 4 : vw;
            constexpr int KS = GU_PIECE_ROWS / 16;
            constexpr int NPRE = K_NPRE;
            uint32_t ga[NPRE][4];
            const uint32_t aoff = (id & 1) * GU_BOX_BYTES + ((id >> 1) * 8 + rr) * (FC * 2) + ct * 16;
            uint32_t ab = 0;
#pragma unroll
            for (int pc = 0; pc < GU_PIECES; pc++) {
                if (real) { mbar_wait(bar_box + (2 + 2 * pc) * 8, 0); mbar_wait(bar_box + (3 + 2 * pc) * 8, 0); }
                ab = (uint32_t)s_misc[2 + pc] + aoff;
#pragma unroll
                for (int k = 0; k < KS; k++) if (pc * KS + k < NPRE) ldsm4t(ga[pc * KS + k], ab + k * 16 * FC * 2);
            }
            static_assert(NPRE == DM / 16, "all fragments preloaded");
            float cs[2][4] = {{0.f, 0.f, 0.f, 0.f}, {0.f, 0.f, 0.f, 0.f}};
#pragma unroll
            for (int k = 0; k < NPRE; k++) mma16816(cs[k & 1], ga[k], 0x3f803f80u, 0x3f803f80u);
            const float csg = cs[0][0] + cs[1][0], csu = cs[0][2] + cs[1][2];
            if (lead) TS(10);
            if (real) bar_sync<BAR_XN, 288>();
            if (lead) TS(14);
            float cc[4][4];
#pragma unroll
            for (int i = 0; i < 4; i++) { cc[i][0] = cc[i][1] = cc[i][2] = cc[i][3] = 0.f; }
            const uint32_t bbase = sb + OFF_XN + (rr & 3) * WPITCH + (rr >> 2) * 64 + id * 16;
#pragma unroll
            for (int k4 = DM / 64 - 1; k4 >= 0; k4--) {
                uint32_t bf[4];
                ldsm4(bf, bbase + k4 * 128);
#pragma unroll
                for (int j = 0; j < 4; j++) {
                    const int ks = 4 * k4 + j;
                    if (ks < NPRE) mma16816(cc[j], ga[ks < NPRE ? ks : 0], bf[2 * (j & 1)], bf[2 * (j & 1) + 1]);
                    else {
                        uint32_t al[4];
                        ldsm4t(al, ab + (ks - 2 * KS) * 16 * FC * 2);
                        mma16816(cc[j], al, bf[2 * (j & 1)], bf[2 * (j & 1) + 1]);
                    }
                }
            }
            float c[4];
#pragma unroll
            for (int e = 0; e < 4; e++) c[e] = (cc[0][e] + cc[1][e]) + __shfl_xor_sync(0xffffffffu, cc[2][e] + cc[3][e], 2);
            if (real) bar_sync<BAR_ST, 288>();
            if (t < 2) {
                __nv_bfloat16* s_act = reinterpret_cast<__nv_bfloat16*>(smem + OFF_ACT);
                const float4 st4 = reinterpret_cast<const float4*>(s_comb + 256)[t];
#pragma unroll
                for (int e = 0; e < 2; e++) {
                    const float mb = e ? st4.z : st4.x, rs = e ? st4.w : st4.y;
                    const float gg = bfr((c[e] - mb * csg) * rs), uu = bfr((c[2 + e] - mb * csu) * rs);
                    const float inner = 0.7978845608028654f * (gg + 0.044715f * gg * gg * gg);
                    const float th = 1.0f - __fdividef(2.0f, ex2(inner * 2.8853900817779268f) + 1.0f);
                    const float ge = bfr(0.5f * gg * (1.0f + th));
                    s_act[(2 * t + e) * (ACT_PITCH / 2) + ct * 8 + g] = __float2bfloat16_rn(ge * uu);
                }
            }
            __syncwarp();
            if (real) bar_arrive<BAR_ACT, 288>();
            if (lead) TS(15);
            if (vw == 8) return;
        } else {
            const int lw = vw - 4;
            uint4 hp[5];
            uint32_t want[5];
#pragma unroll
            for (int j = 0; j < 5; j++) want[j] = (j < 4 || lane < 16) ? real : 0u;
            poll_pkts<5, false>(hp, want, tag, [&](int j) { return g_h + ((cta % HREP) * NB + lw) * (DM / 4) + lane + 32 * j; });
#pragma unroll
            for (int j = 0; j < 5; j++)
                if (j < 4 || lane < 16) *reinterpret_cast<uint2*>(smem + OFF_XN + lw * WPITCH + (lane + 32 * j) * 8) = make_uint2(hp[j].x, hp[j].y);
            __syncwarp();
            if (real) bar_arrive<BAR_XN, 288>();
            if (real && wt == 128) TS(13);
            float4 hv[5];
#pragma unroll
            for (int j = 0; j < 5; j++) hv[j] = make_float4(bf_lo(hp[j].x), bf_hi(hp[j].x), bf_lo(hp[j].y), bf_hi(hp[j].y));
            const float2 st = ln_stats(hv, lane);
            if (lane == 0) reinterpret_cast<float2*>(s_comb + 256)[lw] = st;
            __syncwarp();
            if (real) bar_arrive<BAR_ST, 288>();
#pragma unroll
            for (int j = 0; j < 5; j++) if (want[j]) reinterpret_cast<float4*>(s_x + lw * DM)[lane + 32 * j] = hv[j];
            uint32_t da[9][2][4];
            if (real) { mbar_wait(bar_box + 8 * 8, 0); mbar_wait(bar_box + 9 * 8, 0); }
            const int jc = lw * 2 + (id & 1);
#pragma unroll
            for (int i = 0; i < 9; i++) {
                const uint32_t ad = sb + OFF_DN + ((id >> 1) * 8 + rr) * WROW + i * 128 + ((jc ^ ((rr + i) & 7)) << 4);
                ldsm4t(da[i][0], ad);
                ldsm4t(da[i][1], ad + 16 * WROW);
            }
            if (real) bar_sync<BAR_ACT, 288>();
            if (real && wt == 128) TS(16);
            uint32_t ba[5];
            const uint32_t* s_act32 = reinterpret_cast<const uint32_t*>(smem + OFF_ACT + (g & 3) * ACT_PITCH);
#pragma unroll
            for (int k = 0; k < 5; k++) ba[k] = s_act32[k * 4 + t];
            float c[9][4];
#pragma unroll
            for (int i = 0; i < 9; i++) { c[i][0] = c[i][1] = c[i][2] = c[i][3] = 0.f; mma16816(c[i], da[i][0], ba[0], ba[1]); }
#pragma unroll
            for (int i = 0; i < 9; i++) mma16816(c[i], da[i][1], ba[2], ba[3]);
            if (real) mbar_wait(bar_box + 10 * 8, 0);
            if (real && wt == 128) TS(17);
#pragma unroll
            for (int i = 0; i < 9; i += 2) {
                const int ci = (i + 1 < 9) ? i + (id >> 1) : i;
                uint32_t a2[4];
                ldsm4t(a2, sb + OFF_DN + (32 + rr) * WROW + ci * 128 + ((jc ^ ((rr + ci) & 7)) << 4));
                mma1688(c[i], a2[0], a2[1], ba[4]);
                if (i + 1 < 9) mma1688(c[i + 1], a2[2], a2[3], ba[4]);
            }
#pragma unroll
            for (int i = 0; i < 9; i++) send_tile(g_p2 + cta * DM + (lw + 4 * i) * 16, c[i], g, t, otag);
            if (real && wt == 128) TS(18);
        }
        if (cta < NRED) {
            reduce_cols<NFF>(real, g_p2 + cta * 8, s_red, vw, lane, tag);
            if (real) bar_sync<BAR_W, 256>();
            if (lead) TS(19);
            if (vw == 0) {
                const int ob = (cta & 1) * 2 + (lane >> 4), oc = (cta >> 1) * 16 + (lane & 15);
                float a = 0.f;
#pragma unroll
                for (int w = 0; w < 8; w++) a += s_red[w * 32 + rr * 4 + (id & 1) * 2 + (id >> 1)];
                if (real) p.out[ob * DM + oc] = __float2bfloat16_rn(s_x[ob * DM + oc] + bfr(a));
                if (lead) TS(20);
            }
        }
    }
}

typedef CUresult (*EncodeTiledFn)(CUtensorMap*, CUtensorMapDataType, cuuint32_t, void*, const cuuint64_t*, const cuuint64_t*,
                                  const cuuint32_t*, const cuuint32_t*, CUtensorMapInterleave, CUtensorMapSwizzle,
                                  CUtensorMapL2promotion, CUtensorMapFloatOOBfill);

}

extern "C" void kernel_launch(void* const* d_in, const int* in_sizes, int n_in, void* d_out, int out_size) {
    (void)in_sizes; (void)n_in; (void)out_size;
    static EncodeTiledFn encode = nullptr;
    if (!encode) {
        void* fn = nullptr;
        cudaDriverEntryPointQueryResult qr;
        cudaGetDriverEntryPoint("cuTensorMapEncodeTiled", &fn, cudaEnableDefault, &qr);
        encode = (EncodeTiledFn)fn;
        cudaFuncSetAttribute(fused_decode_kernel, cudaFuncAttributeMaxDynamicSharedMemorySize, SMEM_BYTES);
    }
    CUtensorMap tmq, tmo, tmg, tmu, tmd;
    const cuuint32_t estr[3] = {1, 1, 1};
    {
        const cuuint64_t gdim[2] = {(cuuint64_t)(NH * DH), (cuuint64_t)DM};
        const cuuint64_t gstr[1] = {(cuuint64_t)(NH * DH) * 2};
        const cuuint32_t box[2] = {32, 192};
        encode(&tmq, CU_TENSOR_MAP_DATA_TYPE_BFLOAT16, 2, d_in[3], gdim, gstr, box, estr, CU_TENSOR_MAP_INTERLEAVE_NONE,
               CU_TENSOR_MAP_SWIZZLE_64B, CU_TENSOR_MAP_L2_PROMOTION_L2_256B, CU_TENSOR_MAP_FLOAT_OOB_FILL_NONE);
    }
    {
        const cuuint64_t gdim[2] = {(cuuint64_t)DF, (cuuint64_t)DM};
        const cuuint64_t gstr[1] = {(cuuint64_t)DF * 2};
        const cuuint32_t box[2] = {(cuuint32_t)FC, (cuuint32_t)GU_PIECE_ROWS};
        encode(&tmg, CU_TENSOR_MAP_DATA_TYPE_BFLOAT16, 2, d_in[6], gdim, gstr, box, estr, CU_TENSOR_MAP_INTERLEAVE_NONE,
               CU_TENSOR_MAP_SWIZZLE_NONE, CU_TENSOR_MAP_L2_PROMOTION_L2_256B, CU_TENSOR_MAP_FLOAT_OOB_FILL_NONE);
        encode(&tmu, CU_TENSOR_MAP_DATA_TYPE_BFLOAT16, 2, d_in[7], gdim, gstr, box, estr, CU_TENSOR_MAP_INTERLEAVE_NONE,
               CU_TENSOR_MAP_SWIZZLE_NONE, CU_TENSOR_MAP_L2_PROMOTION_L2_256B, CU_TENSOR_MAP_FLOAT_OOB_FILL_NONE);
    }
    {
        const cuuint64_t gstr[2] = {128, (cuuint64_t)WROW};
        const cuuint64_t gdo[3] = {64, 9, (cuuint64_t)(NH * DH)}, gdd[3] = {64, 9, (cuuint64_t)DF};
        const cuuint32_t boxo[3] = {64, 9, 8}, boxd[3] = {64, 9, 8};
        encode(&tmo, CU_TENSOR_MAP_DATA_TYPE_BFLOAT16, 3, d_in[4], gdo, gstr, boxo, estr, CU_TENSOR_MAP_INTERLEAVE_NONE,
               CU_TENSOR_MAP_SWIZZLE_128B, CU_TENSOR_MAP_L2_PROMOTION_L2_128B, CU_TENSOR_MAP_FLOAT_OOB_FILL_NONE);
        encode(&tmd, CU_TENSOR_MAP_DATA_TYPE_BFLOAT16, 3, d_in[8], gdd, gstr, boxd, estr, CU_TENSOR_MAP_INTERLEAVE_NONE,
               CU_TENSOR_MAP_SWIZZLE_128B, CU_TENSOR_MAP_L2_PROMOTION_L2_128B, CU_TENSOR_MAP_FLOAT_OOB_FILL_NONE);
    }
    Params p;
    p.x = (const __nv_bfloat16*)d_in[0];
    p.k = (const char*)d_in[1];
    p.v = (const char*)d_in[2];
    p.out = (__nv_bfloat16*)d_out;
    fused_decode_kernel<<<GRID, NTHR, SMEM_BYTES, cudaStreamPerThread>>>(p, tmq, tmo, tmg, tmu, tmd);
}
```

```cpp
#include <cuda_runtime.h>
#include <cuda_bf16.h>
#include <cuda.h>
#include <stdint.h>

namespace {

#define K_WIN 2
#define K_WIN2 3
#define K_R0 88
#define K_START 1
#define K_HREP 4
#define K_QMODE 0
#define K_QPRE 1
#define K_NPRE 32
#define K_OMAP 1

constexpr int NB = 4, DM = 576, NH = 32, SK = 8192, DH = 128, DF = 4608;
constexpr int KEYS   = 128;
constexpr int IPH    = SK / KEYS;
constexpr int NITEMS = NB * NH * IPH;
constexpr int NS     = 3;
constexpr int SLOT   = KEYS * DH * 2;
constexpr int MT     = KEYS / 16;
constexpr int NTHR   = 320;
constexpr int GRID   = 132;
constexpr int NOP    = 128;
constexpr int FC     = 40;
constexpr int NFF    = (DF + FC - 1) / FC;
constexpr int NRED   = DM / 8;
constexpr int HREP   = K_HREP;
constexpr int WPITCH = DM * 2 + 16;
constexpr int GU_ROWS = 192;
constexpr int GU_BOX = GU_ROWS * FC * 2;
static_assert(2 * GU_BOX <= SLOT && NS * GU_ROWS == DM, "gate/up pieces");

constexpr int WROW     = DM * 2;
constexpr int OFF_RING = 0;
constexpr int OFF_WO   = OFF_RING + NS * SLOT;
constexpr int OFF_DN   = OFF_WO + 32 * WROW;
constexpr int OFF_XN   = OFF_DN + FC * WROW;
constexpr int OFF_X    = OFF_XN + 4 * WPITCH;
constexpr int OFF_COMB = OFF_X + NB * DM * 4;
constexpr int OFF_RED  = OFF_COMB + 8 * 32 * 4 + 32;
constexpr int OFF_ACT  = OFF_RED + 8 * 32 * 4;
constexpr int ACT_PITCH = 112;
constexpr int OFF_BAR  = OFF_ACT + 4 * ACT_PITCH;
constexpr int NBOX     = 11;
constexpr int OFF_MISC = OFF_BAR + (NS + 2 + NBOX) * 8;
constexpr int SMEM_BYTES = OFF_MISC + 64;
static_assert(OFF_WO % 1024 == 0 && OFF_DN % 1024 == 0 && DM * 64 <= 32 * WROW && SLOT <= FC * WROW, "staging");
static_assert(OFF_BAR % 8 == 0 && OFF_COMB % 16 == 0 && OFF_RED % 16 == 0, "align");
static_assert(SMEM_BYTES <= 232448, "smem");

__device__ unsigned int g_ctr_item;
__device__ __align__(128) uint2 g_q[NB * NH * DH / 2];
__device__ __align__(128) uint4 g_ml[NITEMS * 2];
__device__ __align__(128) uint4 g_op[NITEMS * 32];
__device__ __align__(128) uint4 g_p1[NOP * DM];
__device__ __align__(128) uint4 g_h[HREP * NB * DM / 4];
__device__ __align__(128) uint4 g_p2[NFF * DM];

#define TS(i) do {} while (0)

__device__ __forceinline__ uint32_t smem_u32(const void* p) { return (uint32_t)__cvta_generic_to_shared(p); }
__device__ __forceinline__ void mbar_init(uint32_t bar, uint32_t cnt) { asm volatile("mbarrier.init.shared::cta.b64 [%0], %1;" ::"r"(bar), "r"(cnt) : "memory"); }
__device__ __forceinline__ void mbar_expect_tx(uint32_t bar, uint32_t bytes) { asm volatile("mbarrier.arrive.expect_tx.shared::cta.b64 _, [%0], %1;" ::"r"(bar), "r"(bytes) : "memory"); }
__device__ __forceinline__ bool mbar_try(uint32_t bar, uint32_t parity) {
    uint32_t ok;
    asm volatile("{\n.reg .pred p;\nmbarrier.try_wait.parity.shared::cta.b64 p, [%1], %2;\nselp.u32 %0, 1, 0, p;\n}" : "=r"(ok) : "r"(bar), "r"(parity) : "memory");
    return ok != 0;
}
__device__ __forceinline__ void mbar_wait(uint32_t bar, uint32_t parity) {
    uint32_t n = 0;
    while (!mbar_try(bar, parity)) { if (++n > (1u << 24)) __trap(); }
}
__device__ __forceinline__ void bulk_load(uint32_t dst, const void* src, uint32_t bytes, uint32_t bar, uint64_t pol) {
    asm volatile("cp.async.bulk.shared::cluster.global.mbarrier::complete_tx::bytes.L2::cache_hint [%0], [%1], %2, [%3], %4;"
                 ::"r"(dst), "l"(src), "r"(bytes), "r"(bar), "l"(pol) : "memory");
}
__device__ __forceinline__ void tensor_load_2d(uint32_t dst, const CUtensorMap* tm, int c0, int c1, uint32_t bar) {
    asm volatile("cp.async.bulk.tensor.2d.shared::cluster.global.mbarrier::complete_tx::bytes [%0], [%1, {%3, %4}], [%2];"
                 ::"r"(dst), "l"(tm), "r"(bar), "r"(c0), "r"(c1) : "memory");
}
__device__ __forceinline__ void tensor_load_3d(uint32_t dst, const CUtensorMap* tm, int row, uint32_t bar, uint64_t pol) {
    asm volatile("cp.async.bulk.tensor.3d.shared::cluster.global.mbarrier::complete_tx::bytes.L2::cache_hint [%0], [%1, {%3, %3, %4}], [%2], %5;"
                 ::"r"(dst), "l"(tm), "r"(bar), "r"(0), "r"(row), "l"(pol) : "memory");
}
__device__ __forceinline__ void ldsm4(uint32_t (&r)[4], uint32_t addr) {
    asm volatile("ldmatrix.sync.aligned.m8n8.x4.shared.b16 {%0,%1,%2,%3}, [%4];" : "=r"(r[0]), "=r"(r[1]), "=r"(r[2]), "=r"(r[3]) : "r"(addr) : "memory");
}
__device__ __forceinline__ void ldsm4t(uint32_t (&r)[4], uint32_t addr) {
    asm volatile("ldmatrix.sync.aligned.m8n8.x4.trans.shared.b16 {%0,%1,%2,%3}, [%4];" : "=r"(r[0]), "=r"(r[1]), "=r"(r[2]), "=r"(r[3]) : "r"(addr) : "memory");
}
__device__ __forceinline__ void mma16816(float (&c)[4], const uint32_t (&a)[4], uint32_t b0, uint32_t b1) {
    asm volatile("mma.sync.aligned.m16n8k16.row.col.f32.bf16.bf16.f32 {%0,%1,%2,%3}, {%4,%5,%6,%7}, {%8,%9}, {%0,%1,%2,%3};"
                 : "+f"(c[0]), "+f"(c[1]), "+f"(c[2]), "+f"(c[3]) : "r"(a[0]), "r"(a[1]), "r"(a[2]), "r"(a[3]), "r"(b0), "r"(b1));
}
__device__ __forceinline__ void mma1688(float (&c)[4], uint32_t a0, uint32_t a1, uint32_t b0) {
    asm volatile("mma.sync.aligned.m16n8k8.row.col.f32.bf16.bf16.f32 {%0,%1,%2,%3}, {%4,%5}, {%6}, {%0,%1,%2,%3};"
                 : "+f"(c[0]), "+f"(c[1]), "+f"(c[2]), "+f"(c[3]) : "r"(a0), "r"(a1), "r"(b0));
}
__device__ __forceinline__ float bfr(float x) { return __bfloat162float(__float2bfloat16_rn(x)); }
__device__ __forceinline__ uint32_t pack_bf16(float lo, float hi) {
    uint32_t r; asm("cvt.rn.bf16x2.f32 %0, %1, %2;" : "=r"(r) : "f"(hi), "f"(lo)); return r;
}
__device__ __forceinline__ float bf_lo(uint32_t u) { return __uint_as_float(u << 16); }
__device__ __forceinline__ float bf_hi(uint32_t u) { return __uint_as_float(u & 0xffff0000u); }
__device__ __forceinline__ float ex2(float x) { float r; asm("ex2.approx.ftz.f32 %0, %1;" : "=f"(r) : "f"(x)); return r; }

__device__ __forceinline__ void st_pkt_if(uint32_t on, void* p, uint32_t a, uint32_t b, uint32_t c, uint32_t d) {
    asm volatile("{\n.reg .pred p;\n.reg .b64 l, h;\n.reg .b128 v;\nsetp.ne.u32 p, %5, 0;\nmov.b64 l, {%1,%2};\nmov.b64 h, {%3,%4};\nmov.b128 v, {l,h};\n"
                 "@p st.relaxed.gpu.global.b128 [%0], v;\n}" ::"l"(p), "r"(a), "r"(b), "r"(c), "r"(d), "r"(on) : "memory");
}
__device__ __forceinline__ void ld_pkt_if(uint32_t on, uint4& v, const void* p) {
    asm volatile("{\n.reg .pred p;\n.reg .b64 l, h;\n.reg .b128 v;\nsetp.ne.u32 p, %5, 0;\nmov.b64 l, {%0,%1};\nmov.b64 h, {%2,%3};\nmov.b128 v, {l,h};\n"
                 "@p ld.relaxed.gpu.global.b128 v, [%4];\nmov.b128 {l,h}, v;\nmov.b64 {%0,%1}, l;\nmov.b64 {%2,%3}, h;\n}"
                 : "+r"(v.x), "+r"(v.y), "+r"(v.z), "+r"(v.w) : "l"(p), "r"(on) : "memory");
}
__device__ __forceinline__ void st_pkt8(void* p, uint32_t a, uint32_t b) {
    asm volatile("{\n.reg .b64 v;\nmov.b64 v, {%1,%2};\nst.relaxed.gpu.global.b64 [%0], v;\n}" ::"l"(p), "r"(a), "r"(b) : "memory");
}
__device__ __forceinline__ uint2 ld_pkt8(const void* p) {
    uint2 v;
    asm volatile("{\n.reg .b64 v;\nld.relaxed.gpu.global.b64 v, [%2];\nmov.b64 {%0,%1}, v;\n}" : "=r"(v.x), "=r"(v.y) : "l"(p) : "memory");
    return v;
}
__device__ __forceinline__ void st_f4_if(uint32_t on, void* p, float a, float b, float c, float d, uint32_t tag) {
    const uint32_t ud = __float_as_uint(d);
    st_pkt_if(on, p, __byte_perm(__float_as_uint(a), ud, 0x3217), __byte_perm(__float_as_uint(b), ud, 0x3216),
              __byte_perm(__float_as_uint(c), ud, 0x3215), tag);
}
__device__ __forceinline__ float4 unpack_f4(const uint4& v) {
    const uint32_t d = __byte_perm(__byte_perm(v.z, v.y, 0x0400), v.x, 0x4210);
    return make_float4(__uint_as_float(v.x & 0xffffff00u), __uint_as_float(v.y & 0xffffff00u), __uint_as_float(v.z & 0xffffff00u), __uint_as_float(d & 0xffffff00u));
}
template <int N, int NZ, class AddrFn>
__device__ __forceinline__ void poll_pkts(uint4 (&v)[N], uint32_t (&need)[N], uint32_t tag, AddrFn addr) {
#pragma unroll
    for (int i = 0; i < N; i++) v[i] = make_uint4(0u, 0u, 0u, 0u);
    for (uint32_t n = 0;; n++) {
#pragma unroll
        for (int i = 0; i < N; i++) ld_pkt_if(need[i], v[i], addr(i));
        uint32_t any = 0;
#pragma unroll
        for (int i = 0; i < N; i++) { need[i] = ((i < NZ ? v[i].z : v[i].w) != tag) ? need[i] : 0u; any |= need[i]; }
        if (!__any_sync(0xffffffffu, any != 0)) break;
        if (n > (1u << 22)) __trap();
    }
}
template <int ID, int N> __device__ __forceinline__ void bar_sync() { asm volatile("bar.sync %0, %1;" ::"n"(ID), "n"(N) : "memory"); }
template <int ID, int N> __device__ __forceinline__ void bar_arrive() { asm volatile("bar.arrive %0, %1;" ::"n"(ID), "n"(N) : "memory"); }
constexpr int BAR_W = 1;
constexpr int BAR_GO = 2;
constexpr int BAR_FREE = 3;
constexpr int BAR_Q = 6;
constexpr int BAR_C = 7;
constexpr int BAR_XN = 8;
constexpr int BAR_ST = 9;
constexpr int BAR_ACT = 10;
__device__ __forceinline__ float warp_sum(float v) {
#pragma unroll
    for (int o = 16; o > 0; o >>= 1) v += __shfl_xor_sync(0xffffffffu, v, o);
    return v;
}
__device__ __forceinline__ float warp_max(float v) {
#pragma unroll
    for (int o = 16; o > 0; o >>= 1) v = fmaxf(v, __shfl_xor_sync(0xffffffffu, v, o));
    return v;
}
__device__ __forceinline__ float2 ln_stats(const float4 (&v)[5], int lane) {
    const float piv = __shfl_sync(0xffffffffu, v[0].x, 0);
    float s = 0.f, ss = 0.f;
#pragma unroll
    for (int j = 0; j < 5; j++) {
        const float a = v[j].x - piv, b = v[j].y - piv, c = v[j].z - piv, d = v[j].w - piv;
        if (j < 4 || lane < 16) { s += (a + b) + (c + d); ss += (a * a + b * b) + (c * c + d * d); }
    }
#pragma unroll
    for (int o = 16; o > 0; o >>= 1) { s += __shfl_xor_sync(0xffffffffu, s, o); ss += __shfl_xor_sync(0xffffffffu, ss, o); }
    const float dm = s * (1.0f / DM);
    const float var = bfr(fmaxf(ss * (1.0f / DM) - dm * dm, 0.f));
    float sd, rs;
    asm("sqrt.approx.f32 %0, %1;" : "=f"(sd) : "f"(bfr(var + 1e-5f)));
    asm("rcp.approx.f32 %0, %1;" : "=f"(rs) : "f"(bfr(sd)));
    return make_float2(bfr(piv + dm), rs);
}
__device__ __forceinline__ void send_tile(uint32_t on, uint4* dst, const float (&c)[4], int g, int t, uint32_t tag) {
    st_f4_if(t < 2 ? on : 0u, dst + g + 8 * t, c[0], c[1], c[2], c[3], tag);
}
template <int NSRC>
__device__ __forceinline__ void reduce_cols(uint32_t on, const uint4* src, float* s_red, int vw, int lane, uint32_t tag) {
    uint4 v[4];
    uint32_t need[4];
    const int c0 = vw * 4 + (lane >> 3);
#pragma unroll
    for (int i = 0; i < 4; i++) need[i] = (c0 + 32 * i < NSRC) ? on : 0u;
    poll_pkts<4, 0>(v, need, tag, [&](int i) { return src + (c0 + 32 * i) * DM + (lane & 7); });
    float4 a = make_float4(0.f, 0.f, 0.f, 0.f);
#pragma unroll
    for (int i = 0; i < 4; i++) { const float4 f = unpack_f4(v[i]); a.x += f.x; a.y += f.y; a.z += f.z; a.w += f.w; }
#pragma unroll
    for (int o = 8; o <= 16; o <<= 1) {
        a.x += __shfl_xor_sync(0xffffffffu, a.x, o); a.y += __shfl_xor_sync(0xffffffffu, a.y, o);
        a.z += __shfl_xor_sync(0xffffffffu, a.z, o); a.w += __shfl_xor_sync(0xffffffffu, a.w, o);
    }
    if (lane < 8) reinterpret_cast<float4*>(s_red + vw * 32)[lane] = a;
}

__device__ __forceinline__ int oproj_role(int cta) {
    if (!K_OMAP) return cta < NOP ? cta : -1;
    return cta < NFF - (GRID - NOP) ? cta : (cta < NFF ? -1 : cta - (GRID - NOP));
}

struct Params {
    const __nv_bfloat16* x;
    const char* k;
    const char* v;
    __nv_bfloat16* out;
};

__global__ void __launch_bounds__(NTHR, 1)
fused_decode_kernel(const Params p, const __grid_constant__ CUtensorMap tm_q, const __grid_constant__ CUtensorMap tm_o,
                    const __grid_constant__ CUtensorMap tm_gate, const __grid_constant__ CUtensorMap tm_up,
                    const __grid_constant__ CUtensorMap tm_dn) {
    extern __shared__ __align__(1024) uint8_t smem[];
    const uint32_t sb = smem_u32(smem);
    const int tid = threadIdx.x, warp = tid >> 5, lane = tid & 31, cta = blockIdx.x;
    const int g = lane >> 2, t = lane & 3, id = lane >> 3, rr = lane & 7;
    const uint32_t bar_ring = sb + OFF_BAR, bar_wq = bar_ring + NS * 8, bar_box = bar_wq + 8, bar_ext = bar_box + NBOX * 8;
    volatile int* s_misc = reinterpret_cast<volatile int*>(smem + OFF_MISC);
    float* s_x = reinterpret_cast<float*>(smem + OFF_X);
    uint64_t pol;
    asm volatile("createpolicy.fractional.L2::evict_first.b64 %0, 1.0;" : "=l"(pol));

    if (tid == 0) {
        TS(0);
#pragma unroll
        for (int i = 0; i <= NS; i++) mbar_init(bar_ring + i * 8, 1);
        asm volatile("fence.mbarrier_init.release.cluster;" ::: "memory");
        asm volatile("fence.proxy.async.shared::cta;" ::: "memory");
        if (cta < NOP) {
            mbar_expect_tx(bar_wq, DM * 64);
#pragma unroll
            for (int i = 0; i < 3; i++) tensor_load_2d(sb + OFF_WO + i * 192 * 64, &tm_q, cta * 32, i * 192, bar_wq);
        }
        mbar_expect_tx(bar_ring, SLOT);     bulk_load(sb + OFF_RING, p.k + (size_t)cta * SLOT, SLOT, bar_ring, pol);
        mbar_expect_tx(bar_ring + 8, SLOT); bulk_load(sb + OFF_RING + SLOT, p.v + (size_t)cta * SLOT, SLOT, bar_ring + 8, pol);
    }
    if (K_QPRE && (warp == 6 || warp == 7) && t < 2 && cta < NOP) {
        uint2* q = g_q + ((2 * t + (g & 1)) * NH + (cta >> 2)) * (DH / 2) + (cta & 3) * 16 + (warp - 6) * 8 + (g >> 1);
        st_pkt8(q, 0u, 0u);
        st_pkt8(q + 4, 0u, 0u);
    }
    if (warp >= 6) {
        uint2 u[5];
#pragma unroll
        for (int j = 0; j < 5; j++) if (j < 4 || lane < 16) u[j] = __ldg(reinterpret_cast<const uint2*>(p.x + (warp - 6) * DM) + lane + 32 * j);
#pragma unroll
        for (int j = 0; j < 5; j++) if (j < 4 || lane < 16)
            reinterpret_cast<float4*>(s_x + (warp - 6) * DM)[lane + 32 * j] = make_float4(bf_lo(u[j].x), bf_hi(u[j].x), bf_lo(u[j].y), bf_hi(u[j].y));
    } else if (warp == 1) {
        if (lane == 0) {
            unsigned int c;
            asm volatile("ld.relaxed.gpu.global.u32 %0, [%1];" : "=r"(c) : "l"(&g_ctr_item) : "memory");
            s_misc[0] = (int)(c / NITEMS + 1);
            s_misc[1] = 0;
        } else if (lane <= NBOX + 1) {
            mbar_init(bar_wq + lane * 8, 1);
            asm volatile("fence.mbarrier_init.release.cluster;" ::: "memory");
        }
    }
    __syncthreads();
    const uint32_t tag = (uint32_t)s_misc[0];

    if (warp == 0) {
        uint32_t offK[4], offV[4];
#pragma unroll
        for (int j = 0; j < 4; j++) {
            offK[j] = sb + OFF_RING + ((id & 1) * 8 + rr) * 256 + (((2 * j + (id >> 1)) ^ rr) << 4);
            offV[j] = sb + OFF_RING + ((id >> 1) * 8 + rr) * 256 + (((2 * j + (id & 1)) ^ rr) << 4);
        }
        const bool valid = (t == (g >> 1));
        const int odd = g & 1;
        const float SCALE = 0.08838834764831845f, LOG2E = 1.4426950408889634f;
        uint32_t it0 = cta, it1 = GRID + cta, it2 = 0u;
        uint32_t slot = 0, ph = 0, nfree = 0, iter = 0, pend = 0;
        auto load_q = [&](uint2 (&qq)[2], uint32_t item) {
            const uint2* qp = g_q + (min(item, (uint32_t)NITEMS - 1) / IPH) * (DH / 2) + lane;
            qq[0] = ld_pkt8(qp); qq[1] = ld_pkt8(qp + 32);
        };
        auto refill = [&](const char* base, uint32_t item) {
            if (item < (uint32_t)NITEMS) {
                if (lane == 0) { mbar_expect_tx(bar_ring + slot * 8, SLOT); bulk_load(sb + OFF_RING + slot * SLOT, base + (size_t)item * SLOT, SLOT, bar_ring + slot * 8, pol); }
            } else {
                if (nfree == 0) {
                    if (lane == 0) {
                        s_misc[1] = (int)slot; s_misc[2] = (int)(item - NITEMS);
                        if (item - NITEMS == GRID - 1) atomicAdd(&g_ctr_item, (unsigned)GRID);
                        TS(2);
                    }
                    __syncwarp();
                    bar_arrive<BAR_GO, 288>();
                }
                asm volatile("bar.arrive %0, 64;" ::"r"(BAR_FREE + nfree) : "memory");
                nfree++;
            }
            if (++slot == NS) { slot = 0; ph ^= 1; }
        };
        uint2 qn[2];
        if (K_QMODE == 0) mbar_wait(bar_ring, 0);
        if (K_QMODE == 1 && cta < NOP) mbar_wait(bar_wq, 0);
        load_q(qn, it0);
        while (true) {
            for (uint32_t n = 0; __any_sync(0xffffffffu, qn[0].y != tag || qn[1].y != tag); n++) {
                if (n > (1u << 22)) __trap();
                load_q(qn, it0);
            }
            uint32_t qf[16];
#pragma unroll
            for (int c = 0; c < 16; c++) qf[c] = __shfl_sync(0xffffffffu, qn[c >> 3].x, (((c & 7) ^ g) << 2) + t);
            if (it1 < (uint32_t)NITEMS && lane == 0) pend = (atomicAdd(&g_ctr_item, 1u) % NITEMS) + 2 * GRID;
            load_q(qn, it1);
            mbar_wait(bar_ring + slot * 8, ph);
            float sc[MT][4];
#pragma unroll
            for (int m = 0; m < MT; m++) { sc[m][0] = sc[m][1] = sc[m][2] = sc[m][3] = 0.f; }
            {
                const uint32_t so = slot * SLOT;
#pragma unroll
                for (int j = 0; j < 8; j++) {
#pragma unroll
                    for (int m = 0; m < MT; m++) {
                        uint32_t a[4];
                        ldsm4(a, offK[j & 3] + so + m * 4096 + (j >> 2) * 128);
                        mma16816(sc[m], a, qf[2 * j], qf[2 * j + 1]);
                    }
                }
            }
            if (iter < 2) { it2 = __shfl_sync(0xffffffffu, pend, 0); refill(p.k, it2); }
            else { __syncwarp(); refill(p.v, it1); }
            float s[2 * MT];
            float mx = -INFINITY;
#pragma unroll
            for (int m = 0; m < MT; m++) {
                s[2 * m]     = bfr(bfr(odd ? sc[m][1] : sc[m][0]) * SCALE);
                s[2 * m + 1] = bfr(bfr(odd ? sc[m][3] : sc[m][2]) * SCALE);
                mx = fmaxf(mx, fmaxf(s[2 * m], s[2 * m + 1]));
            }
            mx = warp_max(valid ? mx : -INFINITY);
            const float mref = (mx == -INFINITY) ? 0.f : mx;
            float l = 0.f;
            uint32_t pb[2 * MT];
#pragma unroll
            for (int i = 0; i < 2 * MT; i++) {
                const float e = valid ? ex2((s[i] - mref) * LOG2E) : 0.f;
                l += e;
                pb[i] = pack_bf16(e, 0.f) << (odd * 16);
            }
            l = warp_sum(l);
            st_pkt_if(lane < 2, &g_ml[2 * it0 + lane], __float_as_uint(mx), __float_as_uint(l), tag, 0u);
            float acc[8][4];
#pragma unroll
            for (int i = 0; i < 8; i++) { acc[i][0] = acc[i][1] = acc[i][2] = acc[i][3] = 0.f; }
            mbar_wait(iter == 1 ? bar_ext : bar_ring + slot * 8, iter == 1 ? 0u : ph);
            {
                const uint32_t so = iter == 1 ? (uint32_t)(OFF_DN - OFF_RING) : slot * SLOT;
#pragma unroll
                for (int m = 0; m < MT; m++) {
#pragma unroll
                    for (int i = 0; i < 8; i++) {
                        uint32_t a[4];
                        ldsm4t(a, offV[i & 3] + so + m * 4096 + (i >> 2) * 128);
                        mma16816(acc[i], a, pb[2 * m], pb[2 * m + 1]);
                    }
                }
            }
            if (iter >= 2) { it2 = (it1 < (uint32_t)NITEMS) ? __shfl_sync(0xffffffffu, pend, 0) : (uint32_t)NITEMS; refill(p.k, it2); }
            else { __syncwarp(); if (iter == 0) refill(p.v, it2); iter++; }
            float T[16];
#pragma unroll
            for (int i = 0; i < 8; i++) { T[2 * i] = acc[i][0] + acc[i][3]; T[2 * i + 1] = acc[i][2] + acc[i][1]; }
            float U[16];
#pragma unroll
            for (int c = 0; c < 16; c++) if (!(c & 2)) U[c] = T[c] + __shfl_xor_sync(0xffffffffu, T[c ^ 2], 1);
            const float y0 = U[0] + __shfl_xor_sync(0xffffffffu, U[4], 2), y1 = U[1] + __shfl_xor_sync(0xffffffffu, U[5], 2);
            const float y2 = U[8] + __shfl_xor_sync(0xffffffffu, U[12], 2), y3 = U[9] + __shfl_xor_sync(0xffffffffu, U[13], 2);
            st_f4_if(1u, g_op + (size_t)it0 * 32 + t * 8 + g, y0, y1, y2, y3, tag);
            if (it1 >= (uint32_t)NITEMS) break;
            it0 = it1; it1 = it2;
        }
        if (lane == 0) TS(3);
        if (cta >= NFF) return;
    } else if (warp == 1) {
        if (lane == 0) {
            asm volatile("prefetch.tensormap [%0];" ::"l"(&tm_o) : "memory");
            asm volatile("prefetch.tensormap [%0];" ::"l"(&tm_gate) : "memory");
            asm volatile("prefetch.tensormap [%0];" ::"l"(&tm_up) : "memory");
            asm volatile("prefetch.tensormap [%0];" ::"l"(&tm_dn) : "memory");
        }
        mbar_wait(bar_ring, 0);
        if (lane == 0) {
            const size_t off = (size_t)(GRID + cta) * SLOT;
            mbar_expect_tx(bar_ring + 16, SLOT); bulk_load(sb + OFF_RING + 2 * SLOT, p.k + off, SLOT, bar_ring + 16, pol);
            mbar_expect_tx(bar_ext, SLOT);       bulk_load(sb + OFF_DN, p.v + off, SLOT, bar_ext, pol);
        }
        bar_sync<BAR_FREE, 64>();
        const int slot0 = s_misc[1], opr = oproj_role(cta);
        const int box0 = opr >= 0 ? 0 : 2, nbox = cta < NFF ? NBOX : 2;
        const int win = (s_misc[2] < K_R0) ? K_WIN : K_WIN2;
        if (K_START >= 1) bar_sync<BAR_FREE + 1, 64>();
#pragma unroll
        for (int i = 0; i < NBOX; i++) {
            const int pc = (i - 2) >> 1;
            if (i == 4 && K_START < 1) bar_sync<BAR_FREE + 1, 64>();
            if (i == 6) bar_sync<BAR_FREE + 2, 64>();
            if (i >= box0 && i < nbox) {
                if (i >= box0 + win) mbar_wait(bar_box + (i - win) * 8, 0);
                if (lane == 0) {
                    const uint32_t bar = bar_box + i * 8;
                    if (i < 2) {
                        mbar_expect_tx(bar, 16 * WROW);
                        const int r0 = (opr >> 2) * DH + (opr & 3) * 16 + i * 64;
                        tensor_load_3d(sb + OFF_WO + i * 16 * WROW, &tm_o, r0, bar, pol);
                        tensor_load_3d(sb + OFF_WO + (i * 16 + 8) * WROW, &tm_o, r0 + 8, bar, pol);
                    } else if (i < 8) {
                        mbar_expect_tx(bar, GU_BOX);
                        tensor_load_2d(sb + OFF_RING + ((slot0 + pc) % NS) * SLOT + (i & 1) * GU_BOX, (i & 1) ? &tm_up : &tm_gate, cta * FC, pc * GU_ROWS, bar);
                    } else {
                        const int r0 = (i - 8) * 16;
                        mbar_expect_tx(bar, (i < 10 ? 16 : 8) * WROW);
                        tensor_load_3d(sb + OFF_DN + r0 * WROW, &tm_dn, cta * FC + r0, bar, pol);
                        if (i < 10) tensor_load_3d(sb + OFF_DN + (r0 + 8) * WROW, &tm_dn, cta * FC + r0 + 8, bar, pol);
                    }
                }
                __syncwarp();
            }
        }
        return;
    }

    const int vw = (warp == 0) ? 8 : warp - 2, wt = tid - 64;
    if (vw >= 4 && vw < 8 && cta < NOP) {
        const int w2 = vw - 4;
        float4 xv[5];
#pragma unroll
        for (int j = 0; j < 5; j++) xv[j] = reinterpret_cast<const float4*>(s_x + w2 * DM)[(j < 4 || lane < 16) ? lane + 32 * j : lane];
        const float2 st = ln_stats(xv, lane);
#pragma unroll
        for (int j = 0; j < 5; j++) {
            uint2 o;
            o.x = pack_bf16(bfr(xv[j].x - st.x) * st.y, bfr(xv[j].y - st.x) * st.y);
            o.y = pack_bf16(bfr(xv[j].z - st.x) * st.y, bfr(xv[j].w - st.x) * st.y);
            if (j < 4 || lane < 16) *reinterpret_cast<uint2*>(smem + OFF_XN + w2 * WPITCH + (lane + 32 * j) * 8) = o;
        }
        bar_sync<BAR_Q, 128>();
        if (w2 < 2) {
            mbar_wait(bar_wq, 0);
            if (wt == 128) TS(24);
            float c[2][4] = {{0.f, 0.f, 0.f, 0.f}, {0.f, 0.f, 0.f, 0.f}};
            const uint32_t bbase = sb + OFF_XN + (rr & 3) * WPITCH + id * 16;
            const uint32_t abase = sb + OFF_WO + ((id >> 1) * 8 + rr) * 64 + (((2 * w2 + (id & 1)) ^ (rr >> 1)) << 4);
#pragma unroll 2
            for (int k2 = 0; k2 < DM / 32; k2++) {
                uint32_t bf[4], a0[4], a1[4];
                ldsm4(bf, bbase + k2 * 64);
                ldsm4t(a0, abase + k2 * 2048);
                ldsm4t(a1, abase + k2 * 2048 + 1024);
                mma16816(c[0], a0, bf[0], bf[1]);
                mma16816(c[1], a1, bf[2], bf[3]);
            }
            const bool od = g & 1;
            const float v0 = c[0][0] + c[1][0], v1 = c[0][1] + c[1][1], v2 = c[0][2] + c[1][2], v3 = c[0][3] + c[1][3];
            const float r0 = __shfl_xor_sync(0xffffffffu, od ? v0 : v1, 4), r1 = __shfl_xor_sync(0xffffffffu, od ? v2 : v3, 4);
            if (t < 2) {
                uint2* q = g_q + ((2 * t + (g & 1)) * NH + (cta >> 2)) * (DH / 2) + (cta & 3) * 16 + w2 * 8 + (g >> 1);
                st_pkt8(q, od ? pack_bf16(r0, v1) : pack_bf16(v0, r0), tag);
                st_pkt8(q + 4, od ? pack_bf16(r1, v3) : pack_bf16(v2, r1), tag);
            }
            if (wt == 128) TS(26);
        }
    }
    float* s_comb = reinterpret_cast<float*>(smem + OFF_COMB);
    float* s_red = reinterpret_cast<float*>(smem + OFF_RED);
#pragma unroll 1
    for (uint32_t pass = (vw == 8) ? 1u : 0u; pass < 2; pass++) {
        uint32_t real;
        asm volatile("mov.u32 %0, %1;" : "=r"(real) : "r"(pass));
        int lane, rank;
        asm volatile("mov.u32 %0, %laneid;" : "=r"(lane));
        asm volatile("mov.u32 %0, %ctaid.x;" : "=r"(rank));
        const int g = lane >> 2, t = lane & 3, id = lane >> 3, rr = lane & 7;
        const bool lead = real && wt == 0;
        if (vw < 8) {
            if (real) {
                const int o = oproj_role(rank);
                for (int n = wt; n < DM; n += 256) {
                    st_pkt_if(o >= 0, g_p1 + o * DM + n, 0u, 0u, 0u, 0u);
                    st_pkt_if(rank < NFF, g_p2 + rank * DM + n, 0u, 0u, 0u, 0u);
                }
                if (vw == 0) {
#pragma unroll
                    for (int r = 0; r < (HREP + 3) / 4; r++)
                        st_pkt_if(4 * r + t < HREP && rank < NRED, g_h + ((4 * r + t) * NB + (rank & 1) * 2 + (lane >> 4)) * (DM / 4) + (rank >> 1) * 4 + (g & 3), 0u, 0u, 0u, 0u);
                }
                bar_sync<BAR_GO, 288>();
            } else bar_sync<BAR_W, 256>();
        }
        if (vw < 8) {
            if (lead) TS(8);
            const int opr = oproj_role(rank);
            if (opr >= 0) {
            constexpr int PW = IPH / 2;
            constexpr int NML = IPH / 32, NOV = PW / 4;
            const int half = vw & 1;
            const int base = ((vw >> 1) * NH + (opr >> 2)) * IPH;
            uint4 pk[NML + NOV];
            {
                uint32_t need[NML + NOV];
#pragma unroll
                for (int i = 0; i < NML + NOV; i++) need[i] = real;
                const uint4* pml = g_ml + 2 * (base + lane);
                const uint4* pov = g_op + (size_t)(base + half * PW + id) * 32 + (opr & 3) * 8 + rr;
                poll_pkts<NML + NOV, NML>(pk, need, tag, [&](int i) { return i < NML ? pml + i * 64 : pov + (i - NML) * 128; });
            }
            if (real && wt == 224) TS(27);
            float M = __uint_as_float(pk[0].x);
#pragma unroll
            for (int i = 1; i < NML; i++) M = fmaxf(M, __uint_as_float(pk[i].x));
            M = warp_max(M);
            float wgt[NML], L = 0.f;
#pragma unroll
            for (int i = 0; i < NML; i++) { wgt[i] = ex2((__uint_as_float(pk[i].x) - M) * 1.4426950408889634f); L += wgt[i] * __uint_as_float(pk[i].y); }
            float4 a = make_float4(0.f, 0.f, 0.f, 0.f);
#pragma unroll
            for (int i = 0; i < NOV; i++) {
                const int j = i * 4;
                const float wsel = half ? wgt[(PW + j) / 32] : wgt[j / 32];
                const float w = __shfl_sync(0xffffffffu, wsel, ((half * PW + j) & 31) + id);
                const float4 o4 = unpack_f4(pk[NML + i]);
                a.x = fmaf(w, o4.x, a.x); a.y = fmaf(w, o4.y, a.y); a.z = fmaf(w, o4.z, a.z); a.w = fmaf(w, o4.w, a.w);
            }
            L = warp_sum(L);
#pragma unroll
            for (int o = 8; o <= 16; o <<= 1) {
                a.x += __shfl_xor_sync(0xffffffffu, a.x, o); a.y += __shfl_xor_sync(0xffffffffu, a.y, o);
                a.z += __shfl_xor_sync(0xffffffffu, a.z, o); a.w += __shfl_xor_sync(0xffffffffu, a.w, o);
            }
            const float inv = __fdividef(1.0f, L);
            if (lane < 8) reinterpret_cast<float4*>(s_comb + vw * 32)[lane] = make_float4(a.x * inv, a.y * inv, a.z * inv, a.w * inv);
            if (vw < 6) {
                uint32_t wa[6][2][4];
                if (real) { mbar_wait(bar_box, 0); mbar_wait(bar_box + 8, 0); }
#pragma unroll
                for (int i = 0; i < 6; i++) {
                    const int mt = vw + 6 * i;
                    const uint32_t ad = sb + OFF_WO + ((id >> 1) * 8 + rr) * WROW + (mt >> 2) * 128 + ((((mt & 3) * 2 + (id & 1)) ^ ((rr + (mt >> 2)) & 7)) << 4);
                    ldsm4t(wa[i][0], ad);
                    ldsm4t(wa[i][1], ad + 16 * WROW);
                }
                if (real) bar_sync<BAR_C, 256>();
                if (lead) TS(9);
                const float4* c0 = reinterpret_cast<const float4*>(s_comb + (g & 3) * 64) + 2 * t;
                const float4 u0 = c0[0], u1 = c0[1], v0 = c0[8], v1 = c0[9];
                const uint32_t bo0 = pack_bf16(u0.x + v0.x, u1.x + v1.x), bo1 = pack_bf16(u0.y + v0.y, u1.y + v1.y);
                const uint32_t bo2 = pack_bf16(u0.z + v0.z, u1.z + v1.z), bo3 = pack_bf16(u0.w + v0.w, u1.w + v1.w);
                float c[6][4];
#pragma unroll
                for (int i = 0; i < 6; i++) { c[i][0] = c[i][1] = c[i][2] = c[i][3] = 0.f; mma16816(c[i], wa[i][0], bo0, bo1); }
#pragma unroll
                for (int i = 0; i < 6; i++) mma16816(c[i], wa[i][1], bo2, bo3);
#pragma unroll
                for (int i = 0; i < 6; i++) send_tile(real, g_p1 + opr * DM + (vw + 6 * i) * 16, c[i], g, t, tag);
            } else {
                __syncwarp();
                if (real) bar_arrive<BAR_C, 256>();
            }
            }
            if (lead) TS(11);
            if (rank >= NFF) continue;
            if (rank < NRED) {
                reduce_cols<NOP>(real, g_p1 + rank * 8, s_red, vw, lane, tag);
                if (real) bar_sync<BAR_W, 256>();
                if (lead) TS(12);
                if (vw == 0) {
                    const int ob = (rank & 1) * 2 + (lane >> 4), oc = (rank >> 1) * 16 + (lane & 15);
                    float a1 = 0.f;
#pragma unroll
                    for (int w = 0; w < 8; w++) a1 += s_red[w * 32 + rr * 4 + (id & 1) * 2 + (id >> 1)];
                    const float h = s_x[ob * DM + oc] + bfr(a1);
                    const uint32_t u = pack_bf16(h, __shfl_down_sync(0xffffffffu, h, 1));
                    const uint32_t u0 = __shfl_sync(0xffffffffu, u, lane & ~3), u2 = __shfl_sync(0xffffffffu, u, (lane & ~3) + 2);
#pragma unroll
                    for (int r = 0; r < (HREP + 3) / 4; r++)
                        st_pkt_if(4 * r + t < HREP ? real : 0u, g_h + ((4 * r + t) * NB + ob) * (DM / 4) + (oc >> 2), u0, u2, tag, 0u);
                }
            }
        }
        if (vw < 4 || vw == 8) {
            const int ct = (vw == 8) ? 4 : vw;
            constexpr int KS = GU_ROWS / 16;
            constexpr int NPRE = K_NPRE;
            uint32_t ga[NPRE][4];
            uint32_t alast = 0;
            const uint32_t aoff = sb + OFF_RING + (id & 1) * GU_BOX + ((id >> 1) * 8 + rr) * (FC * 2) + ct * 16;
            int sl = s_misc[1];
#pragma unroll
            for (int pc = 0; pc < NS; pc++) {
                if (real) { mbar_wait(bar_box + (2 + 2 * pc) * 8, 0); mbar_wait(bar_box + (3 + 2 * pc) * 8, 0); }
                alast = aoff + sl * SLOT;
#pragma unroll
                for (int k = 0; k < KS; k++) if (pc * KS + k < NPRE) ldsm4t(ga[pc * KS + k], alast + k * 16 * FC * 2);
                sl = (sl == NS - 1) ? 0 : sl + 1;
            }
            float cs[2][4] = {{0.f, 0.f, 0.f, 0.f}, {0.f, 0.f, 0.f, 0.f}};
#pragma unroll
            for (int k = 0; k < DM / 16; k++) {
                if (k < NPRE) mma16816(cs[k & 1], ga[k < NPRE ? k : 0], 0x3f803f80u, 0x3f803f80u);
                else { uint32_t al[4]; ldsm4t(al, alast + (k - 2 * KS) * 16 * FC * 2); mma16816(cs[k & 1], al, 0x3f803f80u, 0x3f803f80u); }
            }
            const float csg = cs[0][0] + cs[1][0], csu = cs[0][2] + cs[1][2];
            if (lead) TS(10);
            if (real) bar_sync<BAR_XN, 288>();
            if (lead) TS(14);
            float cc[4][4];
#pragma unroll
            for (int i = 0; i < 4; i++) { cc[i][0] = cc[i][1] = cc[i][2] = cc[i][3] = 0.f; }
            const uint32_t bbase = sb + OFF_XN + (rr & 3) * WPITCH + (rr >> 2) * 64 + id * 16;
#pragma unroll
            for (int k4 = 0; k4 < DM / 64; k4++) {
                uint32_t bf[4];
                ldsm4(bf, bbase + k4 * 128);
#pragma unroll
                for (int j = 0; j < 4; j++) {
                    const int k = 4 * k4 + j;
                    if (k < NPRE) mma16816(cc[j], ga[k < NPRE ? k : 0], bf[2 * (j & 1)], bf[2 * (j & 1) + 1]);
                    else { uint32_t al[4]; ldsm4t(al, alast + (k - 2 * KS) * 16 * FC * 2); mma16816(cc[j], al, bf[2 * (j & 1)], bf[2 * (j & 1) + 1]); }
                }
            }
            float c[4];
#pragma unroll
            for (int e = 0; e < 4; e++) c[e] = (cc[0][e] + cc[1][e]) + __shfl_xor_sync(0xffffffffu, cc[2][e] + cc[3][e], 2);
            if (real) bar_sync<BAR_ST, 288>();
            if (t < 2) {
                __nv_bfloat16* s_act = reinterpret_cast<__nv_bfloat16*>(smem + OFF_ACT);
                const float4 st4 = reinterpret_cast<const float4*>(s_comb + 256)[t];
#pragma unroll
                for (int e = 0; e < 2; e++) {
                    const float mb = e ? st4.z : st4.x, rs = e ? st4.w : st4.y;
                    const float gg = bfr((c[e] - mb * csg) * rs), uu = bfr((c[2 + e] - mb * csu) * rs);
                    const float inner = 0.7978845608028654f * (gg + 0.044715f * gg * gg * gg);
                    const float th = 1.0f - __fdividef(2.0f, ex2(inner * 2.8853900817779268f) + 1.0f);
                    const float ge = bfr(0.5f * gg * (1.0f + th));
                    s_act[(2 * t + e) * (ACT_PITCH / 2) + ct * 8 + g] = __float2bfloat16_rn(ge * uu);
                }
            }
            __syncwarp();
            if (real) bar_arrive<BAR_ACT, 288>();
            if (lead) TS(15);
            if (vw == 8) return;
        } else {
            const int lw = vw - 4;
            uint4 hp[5];
            uint32_t need[5];
#pragma unroll
            for (int j = 0; j < 5; j++) need[j] = (j < 4 || lane < 16) ? real : 0u;
            poll_pkts<5, 5>(hp, need, tag, [&](int j) { return g_h + ((rank % HREP) * NB + lw) * (DM / 4) + lane + 32 * j; });
#pragma unroll
            for (int j = 0; j < 5; j++)
                if (j < 4 || lane < 16) *reinterpret_cast<uint2*>(smem + OFF_XN + lw * WPITCH + (lane + 32 * j) * 8) = make_uint2(hp[j].x, hp[j].y);
            __syncwarp();
            if (real) bar_arrive<BAR_XN, 288>();
            if (real && wt == 128) TS(13);
            float4 hv[5];
#pragma unroll
            for (int j = 0; j < 5; j++) hv[j] = make_float4(bf_lo(hp[j].x), bf_hi(hp[j].x), bf_lo(hp[j].y), bf_hi(hp[j].y));
            const float2 st = ln_stats(hv, lane);
            if (lane == 0) reinterpret_cast<float2*>(s_comb + 256)[lw] = st;
            __syncwarp();
            if (real) bar_arrive<BAR_ST, 288>();
#pragma unroll
            for (int j = 0; j < 5; j++) if (real && (j < 4 || lane < 16)) reinterpret_cast<float4*>(s_x + lw * DM)[lane + 32 * j] = hv[j];
            uint32_t da[9][2][4];
            if (real) { mbar_wait(bar_box + 8 * 8, 0); mbar_wait(bar_box + 9 * 8, 0); }
            const int jc = lw * 2 + (id & 1);
#pragma unroll
            for (int i = 0; i < 9; i++) {
                const uint32_t ad = sb + OFF_DN + ((id >> 1) * 8 + rr) * WROW + i * 128 + ((jc ^ ((rr + i) & 7)) << 4);
                ldsm4t(da[i][0], ad);
                ldsm4t(da[i][1], ad + 16 * WROW);
            }
            if (real) bar_sync<BAR_ACT, 288>();
            if (real && wt == 128) TS(16);
            uint32_t ba[5];
            const uint32_t* s_act32 = reinterpret_cast<const uint32_t*>(smem + OFF_ACT + (g & 3) * ACT_PITCH);
#pragma unroll
            for (int k = 0; k < 5; k++) ba[k] = s_act32[k * 4 + t];
            float c[9][4];
#pragma unroll
            for (int i = 0; i < 9; i++) { c[i][0] = c[i][1] = c[i][2] = c[i][3] = 0.f; mma16816(c[i], da[i][0], ba[0], ba[1]); }
#pragma unroll
            for (int i = 0; i < 9; i++) mma16816(c[i], da[i][1], ba[2], ba[3]);
            if (real) mbar_wait(bar_box + 10 * 8, 0);
            if (real && wt == 128) TS(17);
#pragma unroll
            for (int i = 0; i < 9; i += 2) {
                const int ci = (i + 1 < 9) ? i + (id >> 1) : i;
                uint32_t a2[4];
                ldsm4t(a2, sb + OFF_DN + (32 + rr) * WROW + ci * 128 + ((jc ^ ((rr + ci) & 7)) << 4));
                mma1688(c[i], a2[0], a2[1], ba[4]);
                if (i + 1 < 9) mma1688(c[i + 1], a2[2], a2[3], ba[4]);
            }
#pragma unroll
            for (int i = 0; i < 9; i++) send_tile(real, g_p2 + rank * DM + (lw + 4 * i) * 16, c[i], g, t, tag);
            if (real && wt == 128) TS(18);
        }
        if (rank < NRED) {
            reduce_cols<NFF>(real, g_p2 + rank * 8, s_red, vw, lane, tag);
            if (real) bar_sync<BAR_W, 256>();
            if (lead) TS(19);
            if (vw == 0) {
                const int ob = (rank & 1) * 2 + (lane >> 4), oc = (rank >> 1) * 16 + (lane & 15);
                float a = 0.f;
#pragma unroll
                for (int w = 0; w < 8; w++) a += s_red[w * 32 + rr * 4 + (id & 1) * 2 + (id >> 1)];
                if (real) p.out[ob * DM + oc] = __float2bfloat16_rn(s_x[ob * DM + oc] + bfr(a));
                if (lead) TS(20);
            }
        }
    }
}

typedef CUresult (*EncodeTiledFn)(CUtensorMap*, CUtensorMapDataType, cuuint32_t, void*, const cuuint64_t*, const cuuint64_t*,
                                  const cuuint32_t*, const cuuint32_t*, CUtensorMapInterleave, CUtensorMapSwizzle,
                                  CUtensorMapL2promotion, CUtensorMapFloatOOBfill);

}

extern "C" void kernel_launch(void* const* d_in, const int* in_sizes, int n_in, void* d_out, int out_size) {
    (void)in_sizes; (void)n_in; (void)out_size;
    static EncodeTiledFn encode = nullptr;
    if (!encode) {
        void* fn = nullptr;
        cudaDriverEntryPointQueryResult qr;
        cudaGetDriverEntryPoint("cuTensorMapEncodeTiled", &fn, cudaEnableDefault, &qr);
        encode = (EncodeTiledFn)fn;
        cudaFuncSetAttribute(fused_decode_kernel, cudaFuncAttributeMaxDynamicSharedMemorySize, SMEM_BYTES);
    }
    CUtensorMap tmq, tmo, tmg, tmu, tmd;
    const cuuint32_t estr[3] = {1, 1, 1};
    {
        const cuuint64_t gdim[2] = {(cuuint64_t)(NH * DH), (cuuint64_t)DM};
        const cuuint64_t gstr[1] = {(cuuint64_t)(NH * DH) * 2};
        const cuuint32_t box[2] = {32, 192};
        encode(&tmq, CU_TENSOR_MAP_DATA_TYPE_BFLOAT16, 2, d_in[3], gdim, gstr, box, estr, CU_TENSOR_MAP_INTERLEAVE_NONE,
               CU_TENSOR_MAP_SWIZZLE_64B, CU_TENSOR_MAP_L2_PROMOTION_L2_256B, CU_TENSOR_MAP_FLOAT_OOB_FILL_NONE);
    }
    {
        const cuuint64_t gdim[2] = {(cuuint64_t)DF, (cuuint64_t)DM};
        const cuuint64_t gstr[1] = {(cuuint64_t)DF * 2};
        const cuuint32_t box[2] = {(cuuint32_t)FC, (cuuint32_t)GU_ROWS};
        encode(&tmg, CU_TENSOR_MAP_DATA_TYPE_BFLOAT16, 2, d_in[6], gdim, gstr, box, estr, CU_TENSOR_MAP_INTERLEAVE_NONE,
               CU_TENSOR_MAP_SWIZZLE_NONE, CU_TENSOR_MAP_L2_PROMOTION_L2_128B, CU_TENSOR_MAP_FLOAT_OOB_FILL_NONE);
        encode(&tmu, CU_TENSOR_MAP_DATA_TYPE_BFLOAT16, 2, d_in[7], gdim, gstr, box, estr, CU_TENSOR_MAP_INTERLEAVE_NONE,
               CU_TENSOR_MAP_SWIZZLE_NONE, CU_TENSOR_MAP_L2_PROMOTION_L2_128B, CU_TENSOR_MAP_FLOAT_OOB_FILL_NONE);
    }
    {
        const cuuint64_t gstr[2] = {128, (cuuint64_t)WROW};
        const cuuint64_t gdo[3] = {64, 9, (cuuint64_t)(NH * DH)}, gdd[3] = {64, 9, (cuuint64_t)DF};
        const cuuint32_t box[3] = {64, 9, 8};
        encode(&tmo, CU_TENSOR_MAP_DATA_TYPE_BFLOAT16, 3, d_in[4], gdo, gstr, box, estr, CU_TENSOR_MAP_INTERLEAVE_NONE,
               CU_TENSOR_MAP_SWIZZLE_128B, CU_TENSOR_MAP_L2_PROMOTION_L2_128B, CU_TENSOR_MAP_FLOAT_OOB_FILL_NONE);
        encode(&tmd, CU_TENSOR_MAP_DATA_TYPE_BFLOAT16, 3, d_in[8], gdd, gstr, box, estr, CU_TENSOR_MAP_INTERLEAVE_NONE,
               CU_TENSOR_MAP_SWIZZLE_128B, CU_TENSOR_MAP_L2_PROMOTION_L2_128B, CU_TENSOR_MAP_FLOAT_OOB_FILL_NONE);
    }
    Params p;
    p.x = (const __nv_bfloat16*)d_in[0];
    p.k = (const char*)d_in[1];
    p.v = (const char*)d_in[2];
    p.out = (__nv_bfloat16*)d_out;
    fused_decode_kernel<<<GRID, NTHR, SMEM_BYTES, cudaStreamPerThread>>>(p, tmq, tmo, tmg, tmu, tmd);
}
```

```cpp
#include <cuda_runtime.h>
#include <cuda_bf16.h>
#include <cuda.h>
#include <stdint.h>

namespace {

#define K_WKV 4
#define K_WIN 2
#define K_WIN2 3
#define K_R0 88
#define K_CLAIM 1
#define K_HOLD 2
#define K_HREP 4
#define K_NPRE 32
#define K_OMAP 1

constexpr int NB = 4, DM = 576, NH = 32, SK = 8192, DH = 128, DF = 4608;
constexpr int KEYS   = 128;
constexpr int IPH    = SK / KEYS;
constexpr int NITEMS = NB * NH * IPH;
constexpr int NS     = 4;
constexpr int UNIT   = 16384;
constexpr int SLOT   = KEYS * DH * 2;
constexpr int MT     = KEYS / 16;
constexpr int NTHR   = 320;
constexpr int GRID   = 132;
constexpr int NOP    = 128;
constexpr int FC     = 40;
constexpr int NFF    = (DF + FC - 1) / FC;
constexpr int NRED   = DM / 8;
constexpr int HREP   = K_HREP;
constexpr int WPITCH = DM * 2 + 16;
constexpr int GU_ROWS = 192;
constexpr int GU_BOX = GU_ROWS * FC * 2;
constexpr int GU_PIECES = DM / GU_ROWS;
static_assert(2 * GU_BOX <= SLOT && GU_PIECES < NS && SLOT == 2 * UNIT, "gate/up pieces");

constexpr int WROW     = DM * 2;
constexpr int OFF_RING = 0;
constexpr int OFF_WO   = OFF_RING + NS * SLOT;
constexpr int OFF_DN   = OFF_WO + 32 * WROW;
constexpr int OFF_XN   = OFF_DN + FC * WROW;
constexpr int OFF_X    = OFF_XN + 4 * WPITCH;
constexpr int OFF_Q    = OFF_X + NB * DM * 2;
constexpr int OFF_COMB = OFF_Q + 2 * 512;
constexpr int OFF_RED  = OFF_COMB + 8 * 32 * 4 + 32;
constexpr int OFF_ACT  = OFF_RED + 8 * 32 * 4;
constexpr int ACT_PITCH = 112;
constexpr int OFF_BAR  = OFF_ACT + 4 * ACT_PITCH;
constexpr int NBOX     = 11;
constexpr int OFF_MISC = OFF_BAR + (3 * NS + 1 + NBOX) * 8;
constexpr int SMEM_BYTES = OFF_MISC + 64;
static_assert(OFF_WO % 1024 == 0 && OFF_DN % 1024 == 0 && DM * 64 <= 32 * WROW, "staging");
static_assert(OFF_BAR % 8 == 0 && OFF_COMB % 16 == 0 && OFF_RED % 16 == 0, "align");
static_assert(SMEM_BYTES <= 232448, "smem");

__device__ unsigned int g_ctr_item;
__device__ __align__(128) uint2 g_q[NB * NH * DH / 2];
__device__ __align__(128) uint4 g_ml[NITEMS];
__device__ __align__(128) uint4 g_op[NITEMS * 32];
__device__ __align__(128) uint4 g_p1[NOP * DM];
__device__ __align__(128) uint4 g_h[HREP * NB * DM / 4];
__device__ __align__(128) uint4 g_p2[NFF * DM];

#define TS(i) do {} while (0)

__device__ __forceinline__ uint32_t smem_u32(const void* p) { return (uint32_t)__cvta_generic_to_shared(p); }
__device__ __forceinline__ void mbar_init(uint32_t bar, uint32_t cnt) { asm volatile("mbarrier.init.shared::cta.b64 [%0], %1;" ::"r"(bar), "r"(cnt) : "memory"); }
__device__ __forceinline__ void mbar_expect_tx(uint32_t bar, uint32_t bytes) { asm volatile("mbarrier.arrive.expect_tx.shared::cta.b64 _, [%0], %1;" ::"r"(bar), "r"(bytes) : "memory"); }
__device__ __forceinline__ void mbar_arrive(uint32_t bar) { asm volatile("mbarrier.arrive.shared::cta.b64 _, [%0];" ::"r"(bar) : "memory"); }
__device__ __forceinline__ bool mbar_try(uint32_t bar, uint32_t parity) {
    uint32_t ok;
    asm volatile("{\n.reg .pred p;\nmbarrier.try_wait.parity.shared::cta.b64 p, [%1], %2;\nselp.u32 %0, 1, 0, p;\n}" : "=r"(ok) : "r"(bar), "r"(parity) : "memory");
    return ok != 0;
}
__device__ __forceinline__ void mbar_wait(uint32_t bar, uint32_t parity) {
    uint32_t n = 0;
    while (!mbar_try(bar, parity)) { if (++n > (1u << 24)) __trap(); }
}
__device__ __forceinline__ void bulk_load(uint32_t dst, const void* src, uint32_t bytes, uint32_t bar, uint64_t pol) {
    asm volatile("cp.async.bulk.shared::cluster.global.mbarrier::complete_tx::bytes.L2::cache_hint [%0], [%1], %2, [%3], %4;"
                 ::"r"(dst), "l"(src), "r"(bytes), "r"(bar), "l"(pol) : "memory");
}
__device__ __forceinline__ void bulk_load_plain(uint32_t dst, const void* src, uint32_t bytes, uint32_t bar) {
    asm volatile("cp.async.bulk.shared::cluster.global.mbarrier::complete_tx::bytes [%0], [%1], %2, [%3];"
                 ::"r"(dst), "l"(src), "r"(bytes), "r"(bar) : "memory");
}
__device__ __forceinline__ void tensor_load_2d(uint32_t dst, const CUtensorMap* tm, int c0, int c1, uint32_t bar) {
    asm volatile("cp.async.bulk.tensor.2d.shared::cluster.global.mbarrier::complete_tx::bytes [%0], [%1, {%3, %4}], [%2];"
                 ::"r"(dst), "l"(tm), "r"(bar), "r"(c0), "r"(c1) : "memory");
}
__device__ __forceinline__ void tensor_load_3d(uint32_t dst, const CUtensorMap* tm, int row, uint32_t bar, uint64_t pol) {
    asm volatile("cp.async.bulk.tensor.3d.shared::cluster.global.mbarrier::complete_tx::bytes.L2::cache_hint [%0], [%1, {%3, %3, %4}], [%2], %5;"
                 ::"r"(dst), "l"(tm), "r"(bar), "r"(0), "r"(row), "l"(pol) : "memory");
}
__device__ __forceinline__ void ldsm4(uint32_t (&r)[4], uint32_t addr) {
    asm volatile("ldmatrix.sync.aligned.m8n8.x4.shared.b16 {%0,%1,%2,%3}, [%4];" : "=r"(r[0]), "=r"(r[1]), "=r"(r[2]), "=r"(r[3]) : "r"(addr) : "memory");
}
__device__ __forceinline__ void ldsm4t(uint32_t (&r)[4], uint32_t addr) {
    asm volatile("ldmatrix.sync.aligned.m8n8.x4.trans.shared.b16 {%0,%1,%2,%3}, [%4];" : "=r"(r[0]), "=r"(r[1]), "=r"(r[2]), "=r"(r[3]) : "r"(addr) : "memory");
}
__device__ __forceinline__ void mma16816(float (&c)[4], const uint32_t (&a)[4], uint32_t b0, uint32_t b1) {
    asm volatile("mma.sync.aligned.m16n8k16.row.col.f32.bf16.bf16.f32 {%0,%1,%2,%3}, {%4,%5,%6,%7}, {%8,%9}, {%0,%1,%2,%3};"
                 : "+f"(c[0]), "+f"(c[1]), "+f"(c[2]), "+f"(c[3]) : "r"(a[0]), "r"(a[1]), "r"(a[2]), "r"(a[3]), "r"(b0), "r"(b1));
}
__device__ __forceinline__ void mma1688(float (&c)[4], uint32_t a0, uint32_t a1, uint32_t b0) {
    asm volatile("mma.sync.aligned.m16n8k8.row.col.f32.bf16.bf16.f32 {%0,%1,%2,%3}, {%4,%5}, {%6}, {%0,%1,%2,%3};"
                 : "+f"(c[0]), "+f"(c[1]), "+f"(c[2]), "+f"(c[3]) : "r"(a0), "r"(a1), "r"(b0));
}
__device__ __forceinline__ float bfr(float x) { return __bfloat162float(__float2bfloat16_rn(x)); }
__device__ __forceinline__ uint32_t pack_bf16(float lo, float hi) {
    uint32_t r; asm("cvt.rn.bf16x2.f32 %0, %1, %2;" : "=r"(r) : "f"(hi), "f"(lo)); return r;
}
__device__ __forceinline__ float bf_lo(uint32_t u) { return __uint_as_float(u << 16); }
__device__ __forceinline__ float bf_hi(uint32_t u) { return __uint_as_float(u & 0xffff0000u); }
__device__ __forceinline__ float ex2(float x) { float r; asm("ex2.approx.ftz.f32 %0, %1;" : "=f"(r) : "f"(x)); return r; }

__device__ __forceinline__ void st_pkt_if(uint32_t on, void* p, uint32_t a, uint32_t b, uint32_t c, uint32_t d) {
    asm volatile("{\n.reg .pred p;\n.reg .b64 l, h;\n.reg .b128 v;\nsetp.ne.u32 p, %5, 0;\nmov.b64 l, {%1,%2};\nmov.b64 h, {%3,%4};\nmov.b128 v, {l,h};\n"
                 "@p st.relaxed.gpu.global.b128 [%0], v;\n}" ::"l"(p), "r"(a), "r"(b), "r"(c), "r"(d), "r"(on) : "memory");
}
__device__ __forceinline__ void ld_pkt_if(uint32_t on, uint4& v, const void* p) {
    asm volatile("{\n.reg .pred p;\n.reg .b64 l, h;\n.reg .b128 v;\nsetp.ne.u32 p, %5, 0;\nmov.b64 l, {%0,%1};\nmov.b64 h, {%2,%3};\nmov.b128 v, {l,h};\n"
                 "@p ld.relaxed.gpu.global.b128 v, [%4];\nmov.b128 {l,h}, v;\nmov.b64 {%0,%1}, l;\nmov.b64 {%2,%3}, h;\n}"
                 : "+r"(v.x), "+r"(v.y), "+r"(v.z), "+r"(v.w) : "l"(p), "r"(on) : "memory");
}
__device__ __forceinline__ void st_pkt8(void* p, uint32_t a, uint32_t b) {
    asm volatile("{\n.reg .b64 v;\nmov.b64 v, {%1,%2};\nst.relaxed.gpu.global.b64 [%0], v;\n}" ::"l"(p), "r"(a), "r"(b) : "memory");
}
__device__ __forceinline__ uint2 ld_pkt8(const void* p) {
    uint2 v;
    asm volatile("{\n.reg .b64 v;\nld.relaxed.gpu.global.b64 v, [%2];\nmov.b64 {%0,%1}, v;\n}" : "=r"(v.x), "=r"(v.y) : "l"(p) : "memory");
    return v;
}
__device__ __forceinline__ void st_f4_if(uint32_t on, void* p, float a, float b, float c, float d, uint32_t tag) {
    const uint32_t ud = __float_as_uint(d);
    st_pkt_if(on, p, __byte_perm(__float_as_uint(a), ud, 0x3217), __byte_perm(__float_as_uint(b), ud, 0x3216),
              __byte_perm(__float_as_uint(c), ud, 0x3215), tag);
}
__device__ __forceinline__ float4 unpack_f4(const uint4& v) {
    const uint32_t d = __byte_perm(__byte_perm(v.z, v.y, 0x0400), v.x, 0x4210);
    return make_float4(__uint_as_float(v.x & 0xffffff00u), __uint_as_float(v.y & 0xffffff00u), __uint_as_float(v.z & 0xffffff00u), __uint_as_float(d & 0xffffff00u));
}
template <int N, int NZ, class AddrFn>
__device__ __forceinline__ void poll_pkts(uint4 (&v)[N], uint32_t (&need)[N], uint32_t tag, AddrFn addr) {
#pragma unroll
    for (int i = 0; i < N; i++) v[i] = make_uint4(0u, 0u, 0u, 0u);
    for (uint32_t n = 0;; n++) {
#pragma unroll
        for (int i = 0; i < N; i++) ld_pkt_if(need[i], v[i], addr(i));
        uint32_t any = 0;
#pragma unroll
        for (int i = 0; i < N; i++) { need[i] = ((i < NZ ? v[i].z : v[i].w) != tag) ? need[i] : 0u; any |= need[i]; }
        if (!__any_sync(0xffffffffu, any != 0)) break;
        if (n > (1u << 22)) __trap();
    }
}
template <int ID, int N> __device__ __forceinline__ void bar_sync() { asm volatile("bar.sync %0, %1;" ::"n"(ID), "n"(N) : "memory"); }
template <int ID, int N> __device__ __forceinline__ void bar_arrive() { asm volatile("bar.arrive %0, %1;" ::"n"(ID), "n"(N) : "memory"); }
constexpr int BAR_W = 1;
constexpr int BAR_GO = 2;
constexpr int BAR_Q = 6;
constexpr int BAR_C = 7;
constexpr int BAR_XN = 8;
constexpr int BAR_ST = 9;
constexpr int BAR_ACT = 10;
__device__ __forceinline__ float warp_sum(float v) {
#pragma unroll
    for (int o = 16; o > 0; o >>= 1) v += __shfl_xor_sync(0xffffffffu, v, o);
    return v;
}
__device__ __forceinline__ float warp_max(float v) {
    int i = __float_as_int(v);
    i ^= (i >> 31) & 0x7fffffff;
    i = __reduce_max_sync(0xffffffffu, i);
    i ^= (i >> 31) & 0x7fffffff;
    return __int_as_float(i);
}
__device__ __forceinline__ float2 ln_stats(const float4 (&v)[5], int lane) {
    const float piv = __shfl_sync(0xffffffffu, v[0].x, 0);
    float s = 0.f, ss = 0.f;
#pragma unroll
    for (int j = 0; j < 5; j++) {
        const float a = v[j].x - piv, b = v[j].y - piv, c = v[j].z - piv, d = v[j].w - piv;
        if (j < 4 || lane < 16) { s += (a + b) + (c + d); ss += (a * a + b * b) + (c * c + d * d); }
    }
#pragma unroll
    for (int o = 16; o > 0; o >>= 1) { s += __shfl_xor_sync(0xffffffffu, s, o); ss += __shfl_xor_sync(0xffffffffu, ss, o); }
    const float dm = s * (1.0f / DM);
    const float var = bfr(fmaxf(ss * (1.0f / DM) - dm * dm, 0.f));
    float sd, rs;
    asm("sqrt.approx.f32 %0, %1;" : "=f"(sd) : "f"(bfr(var + 1e-5f)));
    asm("rcp.approx.f32 %0, %1;" : "=f"(rs) : "f"(bfr(sd)));
    return make_float2(bfr(piv + dm), rs);
}
__device__ __forceinline__ void send_tile(uint32_t on, uint4* dst, const float (&c)[4], int g, int t, uint32_t tag) {
    st_f4_if(t < 2 ? on : 0u, dst + g + 8 * t, c[0], c[1], c[2], c[3], tag);
}
template <int NSRC>
__device__ __forceinline__ void reduce_cols(uint32_t on, const uint4* src, float* s_red, int vw, int lane, uint32_t tag) {
    uint4 v[4];
    uint32_t need[4];
    const int c0 = vw * 4 + (lane >> 3);
#pragma unroll
    for (int i = 0; i < 4; i++) need[i] = (c0 + 32 * i < NSRC) ? on : 0u;
    poll_pkts<4, 0>(v, need, tag, [&](int i) { return src + (c0 + 32 * i) * DM + (lane & 7); });
    float4 a = make_float4(0.f, 0.f, 0.f, 0.f);
#pragma unroll
    for (int i = 0; i < 4; i++) { const float4 f = unpack_f4(v[i]); a.x += f.x; a.y += f.y; a.z += f.z; a.w += f.w; }
#pragma unroll
    for (int o = 8; o <= 16; o <<= 1) {
        a.x += __shfl_xor_sync(0xffffffffu, a.x, o); a.y += __shfl_xor_sync(0xffffffffu, a.y, o);
        a.z += __shfl_xor_sync(0xffffffffu, a.z, o); a.w += __shfl_xor_sync(0xffffffffu, a.w, o);
    }
    if (lane < 8) reinterpret_cast<float4*>(s_red + vw * 32)[lane] = a;
}

__device__ __forceinline__ float sum8(const float* r) {
    return ((r[0] + r[32]) + (r[64] + r[96])) + ((r[128] + r[160]) + (r[192] + r[224]));
}

__device__ __forceinline__ int oproj_role(int cta) {
    if (!K_OMAP) return cta < NOP ? cta : -1;
    return cta < NFF - (GRID - NOP) ? cta : (cta < NFF ? -1 : cta - (GRID - NOP));
}

struct Params {
    const __nv_bfloat16* x;
    const char* k;
    const char* v;
    __nv_bfloat16* out;
};

__global__ void __launch_bounds__(NTHR, 1)
fused_decode_kernel(const Params p, const __grid_constant__ CUtensorMap tm_q, const __grid_constant__ CUtensorMap tm_o,
                    const __grid_constant__ CUtensorMap tm_gate, const __grid_constant__ CUtensorMap tm_up,
                    const __grid_constant__ CUtensorMap tm_dn) {
    extern __shared__ __align__(1024) uint8_t smem[];
    const uint32_t sb = smem_u32(smem);
    const int tid = threadIdx.x, warp = tid >> 5, lane = tid & 31, cta = blockIdx.x;
    const int g = lane >> 2, t = lane & 3, id = lane >> 3, rr = lane & 7;
    const uint32_t bar_full = sb + OFF_BAR, bar_empty = bar_full + 2 * NS * 8, bar_wq = bar_empty + NS * 8, bar_box = bar_wq + 8;
    volatile int* s_misc = reinterpret_cast<volatile int*>(smem + OFF_MISC);
    __nv_bfloat16* s_x = reinterpret_cast<__nv_bfloat16*>(smem + OFF_X);
    uint64_t pol;
    asm volatile("createpolicy.fractional.L2::evict_first.b64 %0, 1.0;" : "=l"(pol));
    auto issue_unit = [&](uint32_t u, uint32_t item) {
        const uint32_t bar = bar_full + (u & 7) * 8;
        const char* src = ((u & 2) ? p.v : p.k) + (size_t)item * SLOT + (u & 1) * UNIT;
        if ((u & 3) == 0) {
            s_misc[2 + ((u >> 2) & 1)] = (int)item;
            mbar_expect_tx(bar, UNIT + 512);
            bulk_load(sb + OFF_RING + (u & 7) * UNIT, src, UNIT, bar, pol);
            if (u) bulk_load_plain(sb + OFF_Q + ((u >> 2) & 1) * 512, g_q + (item / IPH) * (DH / 2), 512, bar);
            else bulk_load_plain(sb + OFF_Q, p.x, 512, bar);
        } else {
            mbar_expect_tx(bar, UNIT);
            bulk_load(sb + OFF_RING + (u & 7) * UNIT, src, UNIT, bar, pol);
        }
    };

    if (tid == 32) {
        TS(0);
#pragma unroll
        for (int i = 0; i < K_WKV; i++) mbar_init(bar_full + i * 8, 1);
        mbar_init(bar_wq, 1);
        asm volatile("fence.mbarrier_init.release.cluster;" ::: "memory");
        asm volatile("fence.proxy.async.shared::cta;" ::: "memory");
        if (cta < NOP) {
            mbar_expect_tx(bar_wq, DM * 64);
#pragma unroll
            for (int i = 0; i < 3; i++) tensor_load_2d(sb + OFF_WO + i * 192 * 64, &tm_q, cta * 32, i * 192, bar_wq);
        }
#pragma unroll
        for (int u = 0; u < (K_WKV < 4 ? K_WKV : 4); u++) issue_unit(u, cta);
    }
    if ((warp == 6 || warp == 7) && t < 2 && cta < NOP) {
        uint2* q = g_q + ((2 * t + (g & 1)) * NH + (cta >> 2)) * (DH / 2) + (cta & 3) * 16 + (warp - 6) * 8 + (g >> 1);
        st_pkt8(q, 0u, 0u);
        st_pkt8(q + 4, 0u, 0u);
    }
    if (warp >= 6) {
#pragma unroll
        for (int j = 0; j < 5; j++) if (j < 4 || lane < 16)
            reinterpret_cast<uint2*>(s_x + (warp - 6) * DM)[lane + 32 * j] = __ldg(reinterpret_cast<const uint2*>(p.x + (warp - 6) * DM) + lane + 32 * j);
    } else if (warp == 0) {
        if (lane == 31) {
            unsigned int c;
            asm volatile("ld.relaxed.gpu.global.u32 %0, [%1];" : "=r"(c) : "l"(&g_ctr_item) : "memory");
            s_misc[0] = (int)(c / NITEMS + 1);
            s_misc[1] = 0;
        } else if (lane >= K_WKV && lane < 3 * NS + 1 + NBOX && lane != 3 * NS) {
            mbar_init(bar_full + lane * 8, 1);
            asm volatile("fence.mbarrier_init.release.cluster;" ::: "memory");
        }
    }
    __syncthreads();
    const uint32_t tag = (uint32_t)s_misc[0];

    if (warp == 0) {
        uint32_t offK[4], offV[4];
#pragma unroll
        for (int j = 0; j < 4; j++) {
            offK[j] = sb + OFF_RING + ((id & 1) * 8 + rr) * 256 + (((2 * j + (id >> 1)) ^ rr) << 4);
            offV[j] = sb + OFF_RING + ((id >> 1) * 8 + rr) * 256 + (((2 * j + (id & 1)) ^ rr) << 4);
        }
        const bool valid = (t == (g >> 1));
        const int odd = g & 1;
        const float SCALE = 0.08838834764831845f, LOG2E = 1.4426950408889634f;
        for (uint32_t n = 0;; n++) {
            const uint32_t u0 = (n & 1) * 4, ph = (n >> 1) & 1;
            mbar_wait(bar_full + u0 * 8, ph);
            const uint32_t it0 = (uint32_t)s_misc[2 + (n & 1)];
            if (it0 >= (uint32_t)NITEMS) break;
            uint2 qn[2];
            qn[0] = *reinterpret_cast<const uint2*>(smem + OFF_Q + (n & 1) * 512 + lane * 8);
            qn[1] = *reinterpret_cast<const uint2*>(smem + OFF_Q + (n & 1) * 512 + 256 + lane * 8);
            if (n == 0) qn[0].y = 0;
            for (uint32_t k = 0; __any_sync(0xffffffffu, qn[0].y != tag || qn[1].y != tag); k++) {
                if (k > (1u << 22)) __trap();
                const uint2* qp = g_q + (it0 / IPH) * (DH / 2) + lane;
                qn[0] = ld_pkt8(qp); qn[1] = ld_pkt8(qp + 32);
            }
            uint32_t qf[16];
#pragma unroll
            for (int c = 0; c < 16; c++) qf[c] = __shfl_sync(0xffffffffu, qn[c >> 3].x, (((c & 7) ^ g) << 2) + t);
            mbar_wait(bar_full + (u0 + 1) * 8, ph);
            float sc[MT][4];
#pragma unroll
            for (int m = 0; m < MT; m++) { sc[m][0] = sc[m][1] = sc[m][2] = sc[m][3] = 0.f; }
            {
                const uint32_t so = u0 * UNIT;
#pragma unroll
                for (int j = 0; j < 8; j++) {
#pragma unroll
                    for (int m = 0; m < MT; m++) {
                        uint32_t a[4];
                        ldsm4(a, offK[j & 3] + so + m * 4096 + (j >> 2) * 128);
                        mma16816(sc[m], a, qf[2 * j], qf[2 * j + 1]);
                    }
                }
            }
            __syncwarp();
            if (lane == 0) mbar_arrive(bar_empty + (u0 >> 1) * 8);
            float s[2 * MT];
            float mx = -INFINITY;
#pragma unroll
            for (int m = 0; m < MT; m++) {
                s[2 * m]     = bfr(bfr(odd ? sc[m][1] : sc[m][0]) * SCALE);
                s[2 * m + 1] = bfr(bfr(odd ? sc[m][3] : sc[m][2]) * SCALE);
                mx = fmaxf(mx, fmaxf(s[2 * m], s[2 * m + 1]));
            }
            mx = warp_max(valid ? mx : -INFINITY);
            const float mref = (mx == -INFINITY) ? 0.f : mx;
            float l = 0.f;
            uint32_t pb[2 * MT];
#pragma unroll
            for (int i = 0; i < 2 * MT; i++) {
                const float e = valid ? ex2((s[i] - mref) * LOG2E) : 0.f;
                l += e;
                pb[i] = pack_bf16(e, 0.f) << (odd * 16);
            }
            l = warp_sum(l);
            st_pkt_if(lane == 0, &g_ml[it0], __float_as_uint(mx), __float_as_uint(l), tag, 0u);
            float acc[8][4];
#pragma unroll
            for (int i = 0; i < 8; i++) { acc[i][0] = acc[i][1] = acc[i][2] = acc[i][3] = 0.f; }
            mbar_wait(bar_full + (u0 + 2) * 8, ph);
            mbar_wait(bar_full + (u0 + 3) * 8, ph);
            {
                const uint32_t so = (u0 + 2) * UNIT;
#pragma unroll
                for (int m = 0; m < MT; m++) {
#pragma unroll
                    for (int i = 0; i < 8; i++) {
                        uint32_t a[4];
                        ldsm4t(a, offV[i & 3] + so + m * 4096 + (i >> 2) * 128);
                        mma16816(acc[i], a, pb[2 * m], pb[2 * m + 1]);
                    }
                }
            }
            __syncwarp();
            if (lane == 0) mbar_arrive(bar_empty + ((u0 >> 1) + 1) * 8);
            float T[16];
#pragma unroll
            for (int i = 0; i < 8; i++) { T[2 * i] = acc[i][0] + acc[i][3]; T[2 * i + 1] = acc[i][2] + acc[i][1]; }
            float U[16];
#pragma unroll
            for (int c = 0; c < 16; c++) if (!(c & 2)) U[c] = T[c] + __shfl_xor_sync(0xffffffffu, T[c ^ 2], 1);
            const float y0 = U[0] + __shfl_xor_sync(0xffffffffu, U[4], 2), y1 = U[1] + __shfl_xor_sync(0xffffffffu, U[5], 2);
            const float y2 = U[8] + __shfl_xor_sync(0xffffffffu, U[12], 2), y3 = U[9] + __shfl_xor_sync(0xffffffffu, U[13], 2);
            st_f4_if(1u, g_op + (size_t)it0 * 32 + t * 8 + g, y0, y1, y2, y3, tag);
        }
        if (cta >= NFF) return;
    } else if (warp == 1) {
        if (lane == 0) {
            asm volatile("prefetch.tensormap [%0];" ::"l"(&tm_o) : "memory");
            asm volatile("prefetch.tensormap [%0];" ::"l"(&tm_gate) : "memory");
            asm volatile("prefetch.tensormap [%0];" ::"l"(&tm_up) : "memory");
            asm volatile("prefetch.tensormap [%0];" ::"l"(&tm_dn) : "memory");
        }
        uint32_t item = cta, pend = 0, u = (K_WKV < 4 ? K_WKV : 4);
        auto claim = [&]() {
            asm volatile("{\n.reg .pred p;\nsetp.eq.u32 p, %2, 0;\n@p atom.relaxed.gpu.global.add.u32 %0, [%1], 1;\n}" : "+r"(pend) : "l"(&g_ctr_item + lane), "r"(lane) : "memory");
        };
        if (u > K_CLAIM) claim();
        for (;; u++) {
            if (u >= K_WKV) mbar_wait(bar_full + ((u - K_WKV) & 7) * 8, ((u - K_WKV) >> 3) & 1);
            if (!(u & 1) && u >= 2 * NS) mbar_wait(bar_empty + ((u >> 1) & 3) * 8, ((u >> 3) - 1) & 1);
            if ((u & 3) == 0) {
                item = __shfl_sync(0xffffffffu, pend, 0) % NITEMS + GRID;
                if (item >= (uint32_t)NITEMS) break;
            }
            if (lane == 0) issue_unit(u, item);
            if ((u & 3) == K_CLAIM) claim();
            __syncwarp();
        }
        if (lane == 0) {
            s_misc[2 + ((u >> 2) & 1)] = NITEMS;
            s_misc[1] = (int)((u >> 1) & 3);
            mbar_arrive(bar_full + (u & 7) * 8);
            TS(2);
        }
        __syncwarp();
        bar_arrive<BAR_GO, 288>();
        const int slot0 = (u >> 1) & 3, opr = oproj_role(cta);
        const int box0 = opr >= 0 ? 0 : 2, nbox = cta < NFF ? NBOX : 2;
        const int win = ((int)(item - NITEMS) < K_R0) ? K_WIN : K_WIN2;
#pragma unroll
        for (int i = 0; i < NBOX; i++) {
            const int pc = (i - 2) >> 1;
            if (i >= box0 && i < nbox) {
                if (i == 4 || i == 6) mbar_wait(bar_empty + ((slot0 + pc) & 3) * 8, ((u + 2 * pc) / 8 - 1) & 1);
                if (i >= box0 + win) mbar_wait(bar_box + (i - win) * 8, 0);
                if (i - box0 < K_HOLD) { const uint32_t w = u + (i - box0) - K_HOLD; mbar_wait(bar_full + (w & 7) * 8, (w >> 3) & 1); }
                if (lane == 0) {
                    const uint32_t bar = bar_box + i * 8;
                    if (i < 2) {
                        mbar_expect_tx(bar, 16 * WROW);
                        const int r0 = (opr >> 2) * DH + (opr & 3) * 16 + i * 64;
                        tensor_load_3d(sb + OFF_WO + i * 16 * WROW, &tm_o, r0, bar, pol);
                        tensor_load_3d(sb + OFF_WO + (i * 16 + 8) * WROW, &tm_o, r0 + 8, bar, pol);
                    } else if (i < 8) {
                        mbar_expect_tx(bar, GU_BOX);
                        tensor_load_2d(sb + OFF_RING + ((slot0 + pc) & 3) * SLOT + (i & 1) * GU_BOX, (i & 1) ? &tm_up : &tm_gate, cta * FC, pc * GU_ROWS, bar);
                    } else {
                        const int r0 = (i - 8) * 16;
                        mbar_expect_tx(bar, (i < 10 ? 16 : 8) * WROW);
                        tensor_load_3d(sb + OFF_DN + r0 * WROW, &tm_dn, cta * FC + r0, bar, pol);
                        if (i < 10) tensor_load_3d(sb + OFF_DN + (r0 + 8) * WROW, &tm_dn, cta * FC + r0 + 8, bar, pol);
                    }
                }
                __syncwarp();
            }
        }
        return;
    }

    const int vw = (warp == 0) ? 8 : warp - 2, wt = tid - 64;
    if (vw >= 4 && vw < 8 && cta < NOP) {
        const int w2 = vw - 4;
        float4 xv[5];
#pragma unroll
        for (int j = 0; j < 5; j++) {
            const uint2 u = reinterpret_cast<const uint2*>(s_x + w2 * DM)[(j < 4 || lane < 16) ? lane + 32 * j : lane];
            xv[j] = make_float4(bf_lo(u.x), bf_hi(u.x), bf_lo(u.y), bf_hi(u.y));
        }
        const float2 st = ln_stats(xv, lane);
#pragma unroll
        for (int j = 0; j < 5; j++) {
            uint2 o;
            o.x = pack_bf16(bfr(xv[j].x - st.x) * st.y, bfr(xv[j].y - st.x) * st.y);
            o.y = pack_bf16(bfr(xv[j].z - st.x) * st.y, bfr(xv[j].w - st.x) * st.y);
            if (j < 4 || lane < 16) *reinterpret_cast<uint2*>(smem + OFF_XN + w2 * WPITCH + (lane + 32 * j) * 8) = o;
        }
        bar_sync<BAR_Q, 128>();
        if (w2 < 2) {
            mbar_wait(bar_wq, 0);
            if (wt == 128) TS(24);
            float c[2][4] = {{0.f, 0.f, 0.f, 0.f}, {0.f, 0.f, 0.f, 0.f}};
            const uint32_t bbase = sb + OFF_XN + (rr & 3) * WPITCH + id * 16;
            const uint32_t abase = sb + OFF_WO + ((id >> 1) * 8 + rr) * 64 + (((2 * w2 + (id & 1)) ^ (rr >> 1)) << 4);
#pragma unroll 2
            for (int k2 = 0; k2 < DM / 32; k2++) {
                uint32_t bf[4], a0[4], a1[4];
                ldsm4(bf, bbase + k2 * 64);
                ldsm4t(a0, abase + k2 * 2048);
                ldsm4t(a1, abase + k2 * 2048 + 1024);
                mma16816(c[0], a0, bf[0], bf[1]);
                mma16816(c[1], a1, bf[2], bf[3]);
            }
            const bool od = g & 1;
            const float v0 = c[0][0] + c[1][0], v1 = c[0][1] + c[1][1], v2 = c[0][2] + c[1][2], v3 = c[0][3] + c[1][3];
            const float r0 = __shfl_xor_sync(0xffffffffu, od ? v0 : v1, 4), r1 = __shfl_xor_sync(0xffffffffu, od ? v2 : v3, 4);
            if (t < 2) {
                uint2* q = g_q + ((2 * t + (g & 1)) * NH + (cta >> 2)) * (DH / 2) + (cta & 3) * 16 + w2 * 8 + (g >> 1);
                st_pkt8(q, od ? pack_bf16(r0, v1) : pack_bf16(v0, r0), tag);
                st_pkt8(q + 4, od ? pack_bf16(r1, v3) : pack_bf16(v2, r1), tag);
            }
            if (wt == 128) TS(26);
        }
    }
    float* s_comb = reinterpret_cast<float*>(smem + OFF_COMB);
    float* s_red = reinterpret_cast<float*>(smem + OFF_RED);
#pragma unroll 1
    for (uint32_t pass = (vw == 8) ? 1u : 0u; pass < 2; pass++) {
        uint32_t real;
        asm volatile("mov.u32 %0, %1;" : "=r"(real) : "r"(pass));
        int lane, rank;
        asm volatile("mov.u32 %0, %laneid;" : "=r"(lane));
        asm volatile("mov.u32 %0, %ctaid.x;" : "=r"(rank));
        const int g = lane >> 2, t = lane & 3, id = lane >> 3, rr = lane & 7;
        const bool lead = real && wt == 0;
        if (vw < 8) {
            if (real) {
                const int o = oproj_role(rank);
                for (int n = wt; n < DM; n += 256) {
                    st_pkt_if(o >= 0, g_p1 + o * DM + n, 0u, 0u, 0u, 0u);
                    st_pkt_if(rank < NFF, g_p2 + rank * DM + n, 0u, 0u, 0u, 0u);
                }
                if (vw == 0) {
#pragma unroll
                    for (int r = 0; r < (HREP + 3) / 4; r++)
                        st_pkt_if(4 * r + t < HREP && rank < NRED, g_h + ((4 * r + t) * NB + (rank & 1) * 2 + (lane >> 4)) * (DM / 4) + (rank >> 1) * 4 + (g & 3), 0u, 0u, 0u, 0u);
                }
                bar_sync<BAR_GO, 288>();
            } else bar_sync<BAR_W, 256>();
        }
        if (vw < 8) {
            if (lead) TS(8);
            const int opr = oproj_role(rank);
            if (opr >= 0) {
            constexpr int PW = IPH / 2;
            constexpr int NML = IPH / 32, NOV = PW / 4;
            const int half = vw & 1;
            const int base = ((vw >> 1) * NH + (opr >> 2)) * IPH;
            uint4 pk[NML + NOV];
            {
                uint32_t need[NML + NOV];
#pragma unroll
                for (int i = 0; i < NML + NOV; i++) need[i] = real;
                const uint4* pml = g_ml + base + lane;
                const uint4* pov = g_op + (size_t)(base + half * PW + id) * 32 + (opr & 3) * 8 + rr;
                poll_pkts<NML + NOV, NML>(pk, need, tag, [&](int i) { return i < NML ? pml + i * 32 : pov + (i - NML) * 128; });
            }
            if (real && wt == 224) TS(27);
            float M = __uint_as_float(pk[0].x);
#pragma unroll
            for (int i = 1; i < NML; i++) M = fmaxf(M, __uint_as_float(pk[i].x));
            M = warp_max(M);
            float wgt[NML], L = 0.f;
#pragma unroll
            for (int i = 0; i < NML; i++) { wgt[i] = ex2((__uint_as_float(pk[i].x) - M) * 1.4426950408889634f); L += wgt[i] * __uint_as_float(pk[i].y); }
            float4 a = make_float4(0.f, 0.f, 0.f, 0.f);
#pragma unroll
            for (int i = 0; i < NOV; i++) {
                const int j = i * 4;
                const float wsel = half ? wgt[(PW + j) / 32] : wgt[j / 32];
                const float w = __shfl_sync(0xffffffffu, wsel, ((half * PW + j) & 31) + id);
                const float4 o4 = unpack_f4(pk[NML + i]);
                a.x = fmaf(w, o4.x, a.x); a.y = fmaf(w, o4.y, a.y); a.z = fmaf(w, o4.z, a.z); a.w = fmaf(w, o4.w, a.w);
            }
            L = warp_sum(L);
#pragma unroll
            for (int o = 8; o <= 16; o <<= 1) {
                a.x += __shfl_xor_sync(0xffffffffu, a.x, o); a.y += __shfl_xor_sync(0xffffffffu, a.y, o);
                a.z += __shfl_xor_sync(0xffffffffu, a.z, o); a.w += __shfl_xor_sync(0xffffffffu, a.w, o);
            }
            const float inv = __fdividef(1.0f, L);
            if (lane < 8) reinterpret_cast<float4*>(s_comb + vw * 32)[lane] = make_float4(a.x * inv, a.y * inv, a.z * inv, a.w * inv);
            if (vw < 6) {
                uint32_t wa[6][2][4];
                if (real) { mbar_wait(bar_box, 0); mbar_wait(bar_box + 8, 0); }
#pragma unroll
                for (int i = 0; i < 6; i++) {
                    const int mt = vw + 6 * i;
                    const uint32_t ad = sb + OFF_WO + ((id >> 1) * 8 + rr) * WROW + (mt >> 2) * 128 + ((((mt & 3) * 2 + (id & 1)) ^ ((rr + (mt >> 2)) & 7)) << 4);
                    ldsm4t(wa[i][0], ad);
                    ldsm4t(wa[i][1], ad + 16 * WROW);
                }
                if (real) bar_sync<BAR_C, 256>();
                if (lead) TS(9);
                const float4* c0 = reinterpret_cast<const float4*>(s_comb + (g & 3) * 64) + 2 * t;
                const float4 u0 = c0[0], u1 = c0[1], v0 = c0[8], v1 = c0[9];
                const uint32_t bo0 = pack_bf16(u0.x + v0.x, u1.x + v1.x), bo1 = pack_bf16(u0.y + v0.y, u1.y + v1.y);
                const uint32_t bo2 = pack_bf16(u0.z + v0.z, u1.z + v1.z), bo3 = pack_bf16(u0.w + v0.w, u1.w + v1.w);
                float c[6][4];
#pragma unroll
                for (int i = 0; i < 6; i++) { c[i][0] = c[i][1] = c[i][2] = c[i][3] = 0.f; mma16816(c[i], wa[i][0], bo0, bo1); }
#pragma unroll
                for (int i = 0; i < 6; i++) mma16816(c[i], wa[i][1], bo2, bo3);
#pragma unroll
                for (int i = 0; i < 6; i++) send_tile(real, g_p1 + opr * DM + (vw + 6 * i) * 16, c[i], g, t, tag);
            } else {
                __syncwarp();
                if (real) bar_arrive<BAR_C, 256>();
            }
            }
            if (lead) TS(11);
            if (rank >= NFF) continue;
            if (rank < NRED) {
                reduce_cols<NOP>(real, g_p1 + rank * 8, s_red, vw, lane, tag);
                if (real) bar_sync<BAR_W, 256>();
                if (lead) TS(12);
                if (vw == 0) {
                    const int ob = (rank & 1) * 2 + (lane >> 4), oc = (rank >> 1) * 16 + (lane & 15);
                    const float a1 = sum8(s_red + rr * 4 + (id & 1) * 2 + (id >> 1));
                    const float h = __bfloat162float(s_x[ob * DM + oc]) + bfr(a1);
                    const uint32_t u = pack_bf16(h, __shfl_down_sync(0xffffffffu, h, 1));
                    const uint32_t u0 = __shfl_sync(0xffffffffu, u, lane & ~3), u2 = __shfl_sync(0xffffffffu, u, (lane & ~3) + 2);
#pragma unroll
                    for (int r = 0; r < (HREP + 3) / 4; r++)
                        st_pkt_if(4 * r + t < HREP ? real : 0u, g_h + ((4 * r + t) * NB + ob) * (DM / 4) + (oc >> 2), u0, u2, tag, 0u);
                }
            }
        }
        if (vw < 4 || vw == 8) {
            const int ct = (vw == 8) ? 4 : vw;
            constexpr int KS = GU_ROWS / 16;
            constexpr int NPRE = K_NPRE;
            uint32_t ga[NPRE][4];
            uint32_t alast = 0;
            const uint32_t aoff = sb + OFF_RING + (id & 1) * GU_BOX + ((id >> 1) * 8 + rr) * (FC * 2) + ct * 16;
            int sl = s_misc[1];
#pragma unroll
            for (int pc = 0; pc < GU_PIECES; pc++) {
                if (real) { mbar_wait(bar_box + (2 + 2 * pc) * 8, 0); mbar_wait(bar_box + (3 + 2 * pc) * 8, 0); }
                alast = aoff + sl * SLOT;
#pragma unroll
                for (int k = 0; k < KS; k++) if (pc * KS + k < NPRE) ldsm4t(ga[pc * KS + k], alast + k * 16 * FC * 2);
                sl = (sl + 1) & 3;
            }
            float cs[2][4] = {{0.f, 0.f, 0.f, 0.f}, {0.f, 0.f, 0.f, 0.f}};
#pragma unroll
            for (int k = 0; k < DM / 16; k++) {
                if (k < NPRE) mma16816(cs[k & 1], ga[k < NPRE ? k : 0], 0x3f803f80u, 0x3f803f80u);
                else { uint32_t al[4]; ldsm4t(al, alast + (k - 2 * KS) * 16 * FC * 2); mma16816(cs[k & 1], al, 0x3f803f80u, 0x3f803f80u); }
            }
            const float csg = cs[0][0] + cs[1][0], csu = cs[0][2] + cs[1][2];
            if (lead) TS(10);
            if (real) bar_sync<BAR_XN, 288>();
            if (lead) TS(14);
            float cc[4][4];
#pragma unroll
            for (int i = 0; i < 4; i++) { cc[i][0] = cc[i][1] = cc[i][2] = cc[i][3] = 0.f; }
            const uint32_t bbase = sb + OFF_XN + (rr & 3) * WPITCH + (rr >> 2) * 64 + id * 16;
#pragma unroll
            for (int k4 = 0; k4 < DM / 64; k4++) {
                uint32_t bf[4];
                ldsm4(bf, bbase + k4 * 128);
#pragma unroll
                for (int j = 0; j < 4; j++) {
                    const int k = 4 * k4 + j;
                    if (k < NPRE) mma16816(cc[j], ga[k < NPRE ? k : 0], bf[2 * (j & 1)], bf[2 * (j & 1) + 1]);
                    else { uint32_t al[4]; ldsm4t(al, alast + (k - 2 * KS) * 16 * FC * 2); mma16816(cc[j], al, bf[2 * (j & 1)], bf[2 * (j & 1) + 1]); }
                }
            }
            float c[4];
#pragma unroll
            for (int e = 0; e < 4; e++) c[e] = (cc[0][e] + cc[1][e]) + __shfl_xor_sync(0xffffffffu, cc[2][e] + cc[3][e], 2);
            if (real) bar_sync<BAR_ST, 288>();
            if (t < 2) {
                __nv_bfloat16* s_act = reinterpret_cast<__nv_bfloat16*>(smem + OFF_ACT);
                const float4 st4 = reinterpret_cast<const float4*>(s_comb + 256)[t];
#pragma unroll
                for (int e = 0; e < 2; e++) {
                    const float mb = e ? st4.z : st4.x, rs = e ? st4.w : st4.y;
                    const float gg = bfr((c[e] - mb * csg) * rs), uu = bfr((c[2 + e] - mb * csu) * rs);
                    const float ge = bfr(__fdividef(gg, 1.0f + ex2(gg * fmaf(gg * gg, -0.10294324f, -2.3022082f))));
                    s_act[(2 * t + e) * (ACT_PITCH / 2) + ct * 8 + g] = __float2bfloat16_rn(ge * uu);
                }
            }
            __syncwarp();
            if (real) bar_arrive<BAR_ACT, 288>();
            if (lead) TS(15);
            if (vw == 8) return;
        } else {
            const int lw = vw - 4;
            uint4 hp[5];
            uint32_t need[5];
#pragma unroll
            for (int j = 0; j < 5; j++) need[j] = (j < 4 || lane < 16) ? real : 0u;
            poll_pkts<5, 5>(hp, need, tag, [&](int j) { return g_h + ((rank % HREP) * NB + lw) * (DM / 4) + lane + 32 * j; });
#pragma unroll
            for (int j = 0; j < 5; j++)
                if (j < 4 || lane < 16) *reinterpret_cast<uint2*>(smem + OFF_XN + lw * WPITCH + (lane + 32 * j) * 8) = make_uint2(hp[j].x, hp[j].y);
            __syncwarp();
            if (real) bar_arrive<BAR_XN, 288>();
            if (real && wt == 128) TS(13);
            float4 hv[5];
#pragma unroll
            for (int j = 0; j < 5; j++) hv[j] = make_float4(bf_lo(hp[j].x), bf_hi(hp[j].x), bf_lo(hp[j].y), bf_hi(hp[j].y));
            const float2 st = ln_stats(hv, lane);
            if (lane == 0) reinterpret_cast<float2*>(s_comb + 256)[lw] = st;
            __syncwarp();
            if (real) bar_arrive<BAR_ST, 288>();
#pragma unroll
            for (int j = 0; j < 5; j++) if (real && (j < 4 || lane < 16)) reinterpret_cast<uint2*>(s_x + lw * DM)[lane + 32 * j] = make_uint2(hp[j].x, hp[j].y);
            uint32_t da[9][2][4];
            if (real) { mbar_wait(bar_box + 8 * 8, 0); mbar_wait(bar_box + 9 * 8, 0); }
            const int jc = lw * 2 + (id & 1);
#pragma unroll
            for (int i = 0; i < 9; i++) {
                const uint32_t ad = sb + OFF_DN + ((id >> 1) * 8 + rr) * WROW + i * 128 + ((jc ^ ((rr + i) & 7)) << 4);
                ldsm4t(da[i][0], ad);
                ldsm4t(da[i][1], ad + 16 * WROW);
            }
            if (real) bar_sync<BAR_ACT, 288>();
            if (real && wt == 128) TS(16);
            uint32_t ba[5];
            const uint32_t* s_act32 = reinterpret_cast<const uint32_t*>(smem + OFF_ACT + (g & 3) * ACT_PITCH);
#pragma unroll
            for (int k = 0; k < 5; k++) ba[k] = s_act32[k * 4 + t];
            float c[9][4];
#pragma unroll
            for (int i = 0; i < 9; i++) { c[i][0] = c[i][1] = c[i][2] = c[i][3] = 0.f; mma16816(c[i], da[i][0], ba[0], ba[1]); }
#pragma unroll
            for (int i = 0; i < 9; i++) mma16816(c[i], da[i][1], ba[2], ba[3]);
            if (real) mbar_wait(bar_box + 10 * 8, 0);
            if (real && wt == 128) TS(17);
#pragma unroll
            for (int i = 0; i < 9; i += 2) {
                const int ci = (i + 1 < 9) ? i + (id >> 1) : i;
                uint32_t a2[4];
                ldsm4t(a2, sb + OFF_DN + (32 + rr) * WROW + ci * 128 + ((jc ^ ((rr + ci) & 7)) << 4));
                mma1688(c[i], a2[0], a2[1], ba[4]);
                if (i + 1 < 9) mma1688(c[i + 1], a2[2], a2[3], ba[4]);
            }
#pragma unroll
            for (int i = 0; i < 9; i++) send_tile(real, g_p2 + rank * DM + (lw + 4 * i) * 16, c[i], g, t, tag);
            if (real && wt == 128) TS(18);
        }
        if (rank < NRED) {
            reduce_cols<NFF>(real, g_p2 + rank * 8, s_red, vw, lane, tag);
            if (real) bar_sync<BAR_W, 256>();
            if (lead) TS(19);
            if (vw == 0) {
                const int ob = (rank & 1) * 2 + (lane >> 4), oc = (rank >> 1) * 16 + (lane & 15);
                const float a = sum8(s_red + rr * 4 + (id & 1) * 2 + (id >> 1));
                if (real) p.out[ob * DM + oc] = __float2bfloat16_rn(__bfloat162float(s_x[ob * DM + oc]) + bfr(a));
                if (lead) TS(20);
            }
        }
    }
}

typedef CUresult (*EncodeTiledFn)(CUtensorMap*, CUtensorMapDataType, cuuint32_t, void*, const cuuint64_t*, const cuuint64_t*,
                                  const cuuint32_t*, const cuuint32_t*, CUtensorMapInterleave, CUtensorMapSwizzle,
                                  CUtensorMapL2promotion, CUtensorMapFloatOOBfill);

}

extern "C" void kernel_launch(void* const* d_in, const int* in_sizes, int n_in, void* d_out, int out_size) {
    (void)in_sizes; (void)n_in; (void)out_size;
    static EncodeTiledFn encode = nullptr;
    if (!encode) {
        void* fn = nullptr;
        cudaDriverEntryPointQueryResult qr;
        cudaGetDriverEntryPoint("cuTensorMapEncodeTiled", &fn, cudaEnableDefault, &qr);
        encode = (EncodeTiledFn)fn;
        cudaFuncSetAttribute(fused_decode_kernel, cudaFuncAttributeMaxDynamicSharedMemorySize, SMEM_BYTES);
    }
    CUtensorMap tmq, tmo, tmg, tmu, tmd;
    const cuuint32_t estr[3] = {1, 1, 1};
    {
        const cuuint64_t gdim[2] = {(cuuint64_t)(NH * DH), (cuuint64_t)DM};
        const cuuint64_t gstr[1] = {(cuuint64_t)(NH * DH) * 2};
        const cuuint32_t box[2] = {32, 192};
        encode(&tmq, CU_TENSOR_MAP_DATA_TYPE_BFLOAT16, 2, d_in[3], gdim, gstr, box, estr, CU_TENSOR_MAP_INTERLEAVE_NONE,
               CU_TENSOR_MAP_SWIZZLE_64B, CU_TENSOR_MAP_L2_PROMOTION_L2_256B, CU_TENSOR_MAP_FLOAT_OOB_FILL_NONE);
    }
    {
        const cuuint64_t gdim[2] = {(cuuint64_t)DF, (cuuint64_t)DM};
        const cuuint64_t gstr[1] = {(cuuint64_t)DF * 2};
        const cuuint32_t box[2] = {(cuuint32_t)FC, (cuuint32_t)GU_ROWS};
        encode(&tmg, CU_TENSOR_MAP_DATA_TYPE_BFLOAT16, 2, d_in[6], gdim, gstr, box, estr, CU_TENSOR_MAP_INTERLEAVE_NONE,
               CU_TENSOR_MAP_SWIZZLE_NONE, CU_TENSOR_MAP_L2_PROMOTION_L2_128B, CU_TENSOR_MAP_FLOAT_OOB_FILL_NONE);
        encode(&tmu, CU_TENSOR_MAP_DATA_TYPE_BFLOAT16, 2, d_in[7], gdim, gstr, box, estr, CU_TENSOR_MAP_INTERLEAVE_NONE,
               CU_TENSOR_MAP_SWIZZLE_NONE, CU_TENSOR_MAP_L2_PROMOTION_L2_128B, CU_TENSOR_MAP_FLOAT_OOB_FILL_NONE);
    }
    {
        const cuuint64_t gstr[2] = {128, (cuuint64_t)WROW};
        const cuuint64_t gdo[3] = {64, 9, (cuuint64_t)(NH * DH)}, gdd[3] = {64, 9, (cuuint64_t)DF};
        const cuuint32_t box[3] = {64, 9, 8};
        encode(&tmo, CU_TENSOR_MAP_DATA_TYPE_BFLOAT16, 3, d_in[4], gdo, gstr, box, estr, CU_TENSOR_MAP_INTERLEAVE_NONE,
               CU_TENSOR_MAP_SWIZZLE_128B, CU_TENSOR_MAP_L2_PROMOTION_L2_128B, CU_TENSOR_MAP_FLOAT_OOB_FILL_NONE);
        encode(&tmd, CU_TENSOR_MAP_DATA_TYPE_BFLOAT16, 3, d_in[8], gdd, gstr, box, estr, CU_TENSOR_MAP_INTERLEAVE_NONE,
               CU_TENSOR_MAP_SWIZZLE_128B, CU_TENSOR_MAP_L2_PROMOTION_L2_128B, CU_TENSOR_MAP_FLOAT_OOB_FILL_NONE);
    }
    Params p;
    p.x = (const __nv_bfloat16*)d_in[0];
    p.k = (const char*)d_in[1];
    p.v = (const char*)d_in[2];
    p.out = (__nv_bfloat16*)d_out;
    fused_decode_kernel<<<GRID, NTHR, SMEM_BYTES, cudaStreamPerThread>>>(p, tmq, tmo, tmg, tmu, tmd);
}
```

```cpp
#include <cuda_runtime.h>
#include <cuda_bf16.h>
#include <cuda.h>
#include <stdint.h>

namespace {

#define K_WKV 4
#define K_CLAIM 1
#define K_HOLD 2
#define K_WIN 2
#define K_WIN2 3
#define K_R0 56

constexpr int NB = 4, DM = 576, NH = 32, SK = 8192, DH = 128, DF = 4608;
constexpr int KEYS   = 128;
constexpr int IPH    = SK / KEYS;
constexpr int NITEMS = NB * NH * IPH;
constexpr int NS     = 4;
constexpr int UNIT   = 16384;
constexpr int SLOT   = KEYS * DH * 2;
constexpr int MT     = KEYS / 16;
constexpr int NTHR   = 320;
constexpr int GRID   = 132;
constexpr int NOP    = 128;
constexpr int FC     = 40;
constexpr int NFF    = (DF + FC - 1) / FC;
constexpr int NRED   = DM / 8;
constexpr int HREP   = 4;
constexpr int WPITCH = DM * 2 + 16;
constexpr int GW     = 48;
constexpr int GU_ROWS = 144;
constexpr int GU_BOX = GU_ROWS * GW * 2;
constexpr int GU_PIECES = DM / GU_ROWS;
static_assert(2 * GU_BOX <= SLOT && GU_PIECES <= NS && SLOT == 2 * UNIT, "gate/up pieces");

constexpr int WROW     = DM * 2;
constexpr int OFF_RING = 0;
constexpr int OFF_WO   = OFF_RING + NS * SLOT;
constexpr int OFF_DN   = OFF_WO + 32 * WROW;
constexpr int OFF_XN   = OFF_DN + FC * WROW;
constexpr int OFF_X    = OFF_XN + 4 * WPITCH;
constexpr int OFF_Q    = OFF_X + NB * DM * 2;
constexpr int OFF_COMB = OFF_Q + 2 * 512;
constexpr int OFF_RED  = OFF_COMB + 8 * 32 * 4 + 32;
constexpr int OFF_ACT  = OFF_RED + 8 * 32 * 4;
constexpr int ACT_PITCH = 112;
constexpr int OFF_BAR  = OFF_ACT + 4 * ACT_PITCH;
constexpr int BOX_DN   = 2 + 2 * GU_PIECES;
constexpr int NBOX     = BOX_DN + 3;
constexpr int OFF_MISC = OFF_BAR + (3 * NS + 3 + NBOX) * 8;
constexpr int SMEM_BYTES = OFF_MISC + 64;
static_assert(OFF_WO % 1024 == 0 && OFF_DN % 1024 == 0 && DM * 64 <= 32 * WROW, "staging");
static_assert(OFF_BAR % 8 == 0 && OFF_COMB % 16 == 0 && OFF_RED % 16 == 0, "align");
static_assert(SMEM_BYTES <= 232448, "smem");

__device__ unsigned int g_ctr_item;
__device__ __align__(128) uint2 g_q[NB * NH * DH / 2];
__device__ __align__(128) uint4 g_ml[NITEMS];
__device__ __align__(128) uint4 g_op[NITEMS * 32];
__device__ __align__(128) uint4 g_p1[NOP * DM];
__device__ __align__(128) uint4 g_h[HREP * NB * DM / 4];
__device__ __align__(128) uint4 g_p2[NFF * DM];

#define TS(i) do {} while (0)

__device__ __forceinline__ uint32_t smem_u32(const void* p) { return (uint32_t)__cvta_generic_to_shared(p); }
__device__ __forceinline__ void mbar_init(uint32_t bar, uint32_t cnt) { asm volatile("mbarrier.init.shared::cta.b64 [%0], %1;" ::"r"(bar), "r"(cnt) : "memory"); }
__device__ __forceinline__ void mbar_expect_tx(uint32_t bar, uint32_t bytes) { asm volatile("mbarrier.arrive.expect_tx.shared::cta.b64 _, [%0], %1;" ::"r"(bar), "r"(bytes) : "memory"); }
__device__ __forceinline__ void mbar_arrive(uint32_t bar) { asm volatile("mbarrier.arrive.shared::cta.b64 _, [%0];" ::"r"(bar) : "memory"); }
__device__ __forceinline__ bool mbar_try(uint32_t bar, uint32_t parity) {
    uint32_t ok;
    asm volatile("{\n.reg .pred p;\nmbarrier.try_wait.parity.shared::cta.b64 p, [%1], %2;\nselp.u32 %0, 1, 0, p;\n}" : "=r"(ok) : "r"(bar), "r"(parity) : "memory");
    return ok != 0;
}
__device__ __forceinline__ void mbar_wait(uint32_t bar, uint32_t parity) {
    uint32_t n = 0;
    while (!mbar_try(bar, parity)) { if (++n > (1u << 24)) __trap(); }
}
__device__ __forceinline__ void bulk_load(uint32_t dst, const void* src, uint32_t bytes, uint32_t bar, uint64_t pol) {
    asm volatile("cp.async.bulk.shared::cluster.global.mbarrier::complete_tx::bytes.L2::cache_hint [%0], [%1], %2, [%3], %4;"
                 ::"r"(dst), "l"(src), "r"(bytes), "r"(bar), "l"(pol) : "memory");
}
__device__ __forceinline__ void bulk_load_plain(uint32_t dst, const void* src, uint32_t bytes, uint32_t bar) {
    asm volatile("cp.async.bulk.shared::cluster.global.mbarrier::complete_tx::bytes [%0], [%1], %2, [%3];"
                 ::"r"(dst), "l"(src), "r"(bytes), "r"(bar) : "memory");
}
__device__ __forceinline__ void tensor_load_2d(uint32_t dst, const CUtensorMap* tm, int c0, int c1, uint32_t bar) {
    asm volatile("cp.async.bulk.tensor.2d.shared::cluster.global.mbarrier::complete_tx::bytes [%0], [%1, {%3, %4}], [%2];"
                 ::"r"(dst), "l"(tm), "r"(bar), "r"(c0), "r"(c1) : "memory");
}
__device__ __forceinline__ void tensor_load_3d(uint32_t dst, const CUtensorMap* tm, int row, uint32_t bar, uint64_t pol) {
    asm volatile("cp.async.bulk.tensor.3d.shared::cluster.global.mbarrier::complete_tx::bytes.L2::cache_hint [%0], [%1, {%3, %3, %4}], [%2], %5;"
                 ::"r"(dst), "l"(tm), "r"(bar), "r"(0), "r"(row), "l"(pol) : "memory");
}
__device__ __forceinline__ void ldsm4(uint32_t (&r)[4], uint32_t addr) {
    asm volatile("ldmatrix.sync.aligned.m8n8.x4.shared.b16 {%0,%1,%2,%3}, [%4];" : "=r"(r[0]), "=r"(r[1]), "=r"(r[2]), "=r"(r[3]) : "r"(addr) : "memory");
}
__device__ __forceinline__ void ldsm4t(uint32_t (&r)[4], uint32_t addr) {
    asm volatile("ldmatrix.sync.aligned.m8n8.x4.trans.shared.b16 {%0,%1,%2,%3}, [%4];" : "=r"(r[0]), "=r"(r[1]), "=r"(r[2]), "=r"(r[3]) : "r"(addr) : "memory");
}
__device__ __forceinline__ void mma16816(float (&c)[4], const uint32_t (&a)[4], uint32_t b0, uint32_t b1) {
    asm volatile("mma.sync.aligned.m16n8k16.row.col.f32.bf16.bf16.f32 {%0,%1,%2,%3}, {%4,%5,%6,%7}, {%8,%9}, {%0,%1,%2,%3};"
                 : "+f"(c[0]), "+f"(c[1]), "+f"(c[2]), "+f"(c[3]) : "r"(a[0]), "r"(a[1]), "r"(a[2]), "r"(a[3]), "r"(b0), "r"(b1));
}
__device__ __forceinline__ void mma1688(float (&c)[4], uint32_t a0, uint32_t a1, uint32_t b0) {
    asm volatile("mma.sync.aligned.m16n8k8.row.col.f32.bf16.bf16.f32 {%0,%1,%2,%3}, {%4,%5}, {%6}, {%0,%1,%2,%3};"
                 : "+f"(c[0]), "+f"(c[1]), "+f"(c[2]), "+f"(c[3]) : "r"(a0), "r"(a1), "r"(b0));
}
__device__ __forceinline__ float bfr(float x) { return __bfloat162float(__float2bfloat16_rn(x)); }
__device__ __forceinline__ uint32_t pack_bf16(float lo, float hi) {
    uint32_t r; asm("cvt.rn.bf16x2.f32 %0, %1, %2;" : "=r"(r) : "f"(hi), "f"(lo)); return r;
}
__device__ __forceinline__ float bf_lo(uint32_t u) { return __uint_as_float(u << 16); }
__device__ __forceinline__ float bf_hi(uint32_t u) { return __uint_as_float(u & 0xffff0000u); }
__device__ __forceinline__ float ex2(float x) { float r; asm("ex2.approx.ftz.f32 %0, %1;" : "=f"(r) : "f"(x)); return r; }

__device__ __forceinline__ void st_pkt_if(uint32_t on, void* p, uint32_t a, uint32_t b, uint32_t c, uint32_t d) {
    asm volatile("{\n.reg .pred p;\n.reg .b64 l, h;\n.reg .b128 v;\nsetp.ne.u32 p, %5, 0;\nmov.b64 l, {%1,%2};\nmov.b64 h, {%3,%4};\nmov.b128 v, {l,h};\n"
                 "@p st.relaxed.gpu.global.b128 [%0], v;\n}" ::"l"(p), "r"(a), "r"(b), "r"(c), "r"(d), "r"(on) : "memory");
}
__device__ __forceinline__ void ld_pkt_if(uint32_t on, uint4& v, const void* p) {
    asm volatile("{\n.reg .pred p;\n.reg .b64 l, h;\n.reg .b128 v;\nsetp.ne.u32 p, %5, 0;\nmov.b64 l, {%0,%1};\nmov.b64 h, {%2,%3};\nmov.b128 v, {l,h};\n"
                 "@p ld.relaxed.gpu.global.b128 v, [%4];\nmov.b128 {l,h}, v;\nmov.b64 {%0,%1}, l;\nmov.b64 {%2,%3}, h;\n}"
                 : "+r"(v.x), "+r"(v.y), "+r"(v.z), "+r"(v.w) : "l"(p), "r"(on) : "memory");
}
__device__ __forceinline__ void st_pkt8(void* p, uint32_t a, uint32_t b) {
    asm volatile("{\n.reg .b64 v;\nmov.b64 v, {%1,%2};\nst.relaxed.gpu.global.b64 [%0], v;\n}" ::"l"(p), "r"(a), "r"(b) : "memory");
}
__device__ __forceinline__ uint2 ld_pkt8(const void* p) {
    uint2 v;
    asm volatile("{\n.reg .b64 v;\nld.relaxed.gpu.global.b64 v, [%2];\nmov.b64 {%0,%1}, v;\n}" : "=r"(v.x), "=r"(v.y) : "l"(p) : "memory");
    return v;
}
__device__ __forceinline__ void st_f4_if(uint32_t on, void* p, float a, float b, float c, float d, uint32_t tag) {
    const uint32_t ud = __float_as_uint(d);
    st_pkt_if(on, p, __byte_perm(__float_as_uint(a), ud, 0x3217), __byte_perm(__float_as_uint(b), ud, 0x3216),
              __byte_perm(__float_as_uint(c), ud, 0x3215), tag);
}
__device__ __forceinline__ float4 unpack_f4(const uint4& v) {
    const uint32_t d = __byte_perm(__byte_perm(v.z, v.y, 0x0400), v.x, 0x4210);
    return make_float4(__uint_as_float(v.x & 0xffffff00u), __uint_as_float(v.y & 0xffffff00u), __uint_as_float(v.z & 0xffffff00u), __uint_as_float(d & 0xffffff00u));
}
template <int N, int NZ, class AddrFn>
__device__ __forceinline__ void poll_pkts(uint4 (&v)[N], uint32_t (&need)[N], uint32_t tag, AddrFn addr) {
#pragma unroll
    for (int i = 0; i < N; i++) v[i] = make_uint4(0u, 0u, 0u, 0u);
    for (uint32_t n = 0;; n++) {
#pragma unroll
        for (int i = 0; i < N; i++) ld_pkt_if(need[i], v[i], addr(i));
        uint32_t any = 0;
#pragma unroll
        for (int i = 0; i < N; i++) { need[i] = ((i < NZ ? v[i].z : v[i].w) != tag) ? need[i] : 0u; any |= need[i]; }
        if (!__any_sync(0xffffffffu, any != 0)) break;
        if (n > (1u << 22)) __trap();
    }
}
template <int ID, int N> __device__ __forceinline__ void bar_sync() { asm volatile("bar.sync %0, %1;" ::"n"(ID), "n"(N) : "memory"); }
template <int ID, int N> __device__ __forceinline__ void bar_arrive() { asm volatile("bar.arrive %0, %1;" ::"n"(ID), "n"(N) : "memory"); }
constexpr int BAR_W = 1;
constexpr int BAR_GO = 2;
constexpr int BAR_Q = 6;
constexpr int BAR_C = 7;
constexpr int BAR_XN = 8;
constexpr int BAR_ST = 9;
constexpr int BAR_ACT = 10;
__device__ __forceinline__ float warp_sum(float v) {
#pragma unroll
    for (int o = 16; o > 0; o >>= 1) v += __shfl_xor_sync(0xffffffffu, v, o);
    return v;
}
__device__ __forceinline__ float warp_max(float v) {
    int i = __float_as_int(v);
    i ^= (i >> 31) & 0x7fffffff;
    i = __reduce_max_sync(0xffffffffu, i);
    i ^= (i >> 31) & 0x7fffffff;
    return __int_as_float(i);
}
__device__ __forceinline__ float2 ln_stats(const float4 (&v)[5], int lane) {
    const float piv = __shfl_sync(0xffffffffu, v[0].x, 0);
    float s = 0.f, ss = 0.f;
#pragma unroll
    for (int j = 0; j < 5; j++) {
        const float a = v[j].x - piv, b = v[j].y - piv, c = v[j].z - piv, d = v[j].w - piv;
        if (j < 4 || lane < 16) { s += (a + b) + (c + d); ss += (a * a + b * b) + (c * c + d * d); }
    }
#pragma unroll
    for (int o = 16; o > 0; o >>= 1) { s += __shfl_xor_sync(0xffffffffu, s, o); ss += __shfl_xor_sync(0xffffffffu, ss, o); }
    const float dm = s * (1.0f / DM);
    const float var = bfr(fmaxf(ss * (1.0f / DM) - dm * dm, 0.f));
    float sd, rs;
    asm("sqrt.approx.f32 %0, %1;" : "=f"(sd) : "f"(bfr(var + 1e-5f)));
    asm("rcp.approx.f32 %0, %1;" : "=f"(rs) : "f"(bfr(sd)));
    return make_float2(bfr(piv + dm), rs);
}
__device__ __forceinline__ void send_tile(uint32_t on, uint4* dst, const float (&c)[4], int g, int t, uint32_t tag) {
    st_f4_if(t < 2 ? on : 0u, dst + g + 8 * t, c[0], c[1], c[2], c[3], tag);
}
template <int NSRC>
__device__ __forceinline__ void reduce_cols(uint32_t on, const uint4* src, float* s_red, int vw, int lane, uint32_t tag) {
    uint4 v[4];
    uint32_t need[4];
    const int c0 = vw * 4 + (lane >> 3);
#pragma unroll
    for (int i = 0; i < 4; i++) need[i] = (c0 + 32 * i < NSRC) ? on : 0u;
    poll_pkts<4, 0>(v, need, tag, [&](int i) { return src + (c0 + 32 * i) * DM + (lane & 7); });
    float4 a = make_float4(0.f, 0.f, 0.f, 0.f);
#pragma unroll
    for (int i = 0; i < 4; i++) { const float4 f = unpack_f4(v[i]); a.x += f.x; a.y += f.y; a.z += f.z; a.w += f.w; }
#pragma unroll
    for (int o = 8; o <= 16; o <<= 1) {
        a.x += __shfl_xor_sync(0xffffffffu, a.x, o); a.y += __shfl_xor_sync(0xffffffffu, a.y, o);
        a.z += __shfl_xor_sync(0xffffffffu, a.z, o); a.w += __shfl_xor_sync(0xffffffffu, a.w, o);
    }
    if (lane < 8) reinterpret_cast<float4*>(s_red + vw * 32)[lane] = a;
}

__device__ __forceinline__ float sum8(const float* r) {
    return ((r[0] + r[32]) + (r[64] + r[96])) + ((r[128] + r[160]) + (r[192] + r[224]));
}

__device__ __forceinline__ int oproj_role(int cta) {
    return cta < NFF - (GRID - NOP) ? cta : (cta < NFF ? -1 : cta - (GRID - NOP));
}

struct Params {
    const __nv_bfloat16* x;
    const char* k;
    const char* v;
    __nv_bfloat16* out;
};

__global__ void __launch_bounds__(NTHR, 1)
fused_decode_kernel(const Params p, const __grid_constant__ CUtensorMap tm_q, const __grid_constant__ CUtensorMap tm_o,
                    const __grid_constant__ CUtensorMap tm_gate, const __grid_constant__ CUtensorMap tm_up,
                    const __grid_constant__ CUtensorMap tm_dn) {
    extern __shared__ __align__(1024) uint8_t smem[];
    const uint32_t sb = smem_u32(smem);
    const int tid = threadIdx.x, warp = tid >> 5, lane = tid & 31, cta = blockIdx.x;
    const int g = lane >> 2, t = lane & 3, id = lane >> 3, rr = lane & 7;
    const uint32_t bar_full = sb + OFF_BAR, bar_empty = bar_full + 2 * NS * 8, bar_wq = bar_empty + NS * 8, bar_box = bar_wq + 24;
    volatile int* s_misc = reinterpret_cast<volatile int*>(smem + OFF_MISC);
    __nv_bfloat16* s_x = reinterpret_cast<__nv_bfloat16*>(smem + OFF_X);
    uint64_t pol;
    asm volatile("createpolicy.fractional.L2::evict_first.b64 %0, 1.0;" : "=l"(pol));
    auto issue_unit = [&](uint32_t u, uint32_t item) {
        const uint32_t bar = bar_full + (u & 7) * 8;
        const bool with_q = (u & 3) == 0 && u != 0;
        if ((u & 3) == 0) s_misc[2 + ((u >> 2) & 1)] = (int)item;
        mbar_expect_tx(bar, with_q ? UNIT + 512 : UNIT);
        bulk_load(sb + OFF_RING + (u & 7) * UNIT, ((u & 2) ? p.v : p.k) + (size_t)item * SLOT + (u & 1) * UNIT, UNIT, bar, pol);
        if (with_q) bulk_load_plain(sb + OFF_Q + ((u >> 2) & 1) * 512, g_q + (item / IPH) * (DH / 2), 512, bar);
    };

    if (tid == 32) {
        TS(0);
#pragma unroll
        for (int i = 0; i < K_WKV; i++) mbar_init(bar_full + i * 8, 1);
        mbar_init(bar_wq, 1); mbar_init(bar_wq + 8, 1); mbar_init(bar_wq + 16, 1);
        asm volatile("fence.mbarrier_init.release.cluster;" ::: "memory");
        asm volatile("fence.proxy.async.shared::cta;" ::: "memory");
        if (cta < NOP) {
#pragma unroll
            for (int i = 0; i < 3; i++) {
                mbar_expect_tx(bar_wq + i * 8, 192 * 64);
                tensor_load_2d(sb + OFF_WO + i * 192 * 64, &tm_q, cta * 32, i * 192, bar_wq + i * 8);
            }
        }
#pragma unroll
        for (int u = 0; u < (K_WKV < 4 ? K_WKV : 4); u++) issue_unit(u, cta);
    }
    if ((warp == 6 || warp == 7) && t < 2 && cta < NOP) {
        uint2* q = g_q + ((2 * t + (g & 1)) * NH + (cta >> 2)) * (DH / 2) + (cta & 3) * 16 + (warp - 6) * 8 + (g >> 1);
        st_pkt8(q, 0u, 0u);
        st_pkt8(q + 4, 0u, 0u);
    }
    if (warp >= 6) {
#pragma unroll
        for (int j = 0; j < 5; j++) if (j < 4 || lane < 16)
            reinterpret_cast<uint2*>(s_x + (warp - 6) * DM)[lane + 32 * j] = __ldg(reinterpret_cast<const uint2*>(p.x + (warp - 6) * DM) + lane + 32 * j);
    } else if (warp == 0) {
        if (lane == 31) {
            unsigned int c;
            asm volatile("ld.relaxed.gpu.global.u32 %0, [%1];" : "=r"(c) : "l"(&g_ctr_item) : "memory");
            s_misc[0] = (int)(c / NITEMS + 1);
            s_misc[1] = 0;
        } else if (lane >= K_WKV && lane < 3 * NS + 3 + NBOX && (lane < 3 * NS || lane >= 3 * NS + 3)) {
            mbar_init(bar_full + lane * 8, 1);
            asm volatile("fence.mbarrier_init.release.cluster;" ::: "memory");
        }
    }
    __syncthreads();
    const uint32_t tag = (uint32_t)s_misc[0];

    if (warp == 0) {
        uint32_t offK[4], offV[4];
#pragma unroll
        for (int j = 0; j < 4; j++) {
            offK[j] = sb + OFF_RING + ((id & 1) * 8 + rr) * 256 + (((2 * j + (id >> 1)) ^ rr) << 4);
            offV[j] = sb + OFF_RING + ((id >> 1) * 8 + rr) * 256 + (((2 * j + (id & 1)) ^ rr) << 4);
        }
        const bool valid = (t == (g >> 1));
        const int odd = g & 1;
        const float SCALE = 0.08838834764831845f, LOG2E = 1.4426950408889634f;
        for (uint32_t n = 0;; n++) {
            const uint32_t u0 = (n & 1) * 4, ph = (n >> 1) & 1;
            mbar_wait(bar_full + u0 * 8, ph);
            const uint32_t it0 = (uint32_t)s_misc[2 + (n & 1)];
            if (it0 >= (uint32_t)NITEMS) break;
            uint2 qn[2];
            qn[0] = *reinterpret_cast<const uint2*>(smem + OFF_Q + (n & 1) * 512 + lane * 8);
            qn[1] = *reinterpret_cast<const uint2*>(smem + OFF_Q + (n & 1) * 512 + 256 + lane * 8);
            if (n == 0) qn[0].y = 0;
            for (uint32_t k = 0; __any_sync(0xffffffffu, qn[0].y != tag || qn[1].y != tag); k++) {
                if (k > (1u << 22)) __trap();
                const uint2* qp = g_q + (it0 / IPH) * (DH / 2) + lane;
                qn[0] = ld_pkt8(qp); qn[1] = ld_pkt8(qp + 32);
            }
            uint32_t qf[16];
#pragma unroll
            for (int c = 0; c < 16; c++) qf[c] = __shfl_sync(0xffffffffu, qn[c >> 3].x, (((c & 7) ^ g) << 2) + t);
            mbar_wait(bar_full + (u0 + 1) * 8, ph);
            float sc[MT][4];
#pragma unroll
            for (int m = 0; m < MT; m++) { sc[m][0] = sc[m][1] = sc[m][2] = sc[m][3] = 0.f; }
            {
                const uint32_t so = u0 * UNIT;
#pragma unroll
                for (int j = 0; j < 8; j++) {
#pragma unroll
                    for (int m = 0; m < MT; m++) {
                        uint32_t a[4];
                        ldsm4(a, offK[j & 3] + so + m * 4096 + (j >> 2) * 128);
                        mma16816(sc[m], a, qf[2 * j], qf[2 * j + 1]);
                    }
                }
            }
            __syncwarp();
            if (lane == 0) mbar_arrive(bar_empty + (u0 >> 1) * 8);
            float s[2 * MT];
            float mx = -INFINITY;
#pragma unroll
            for (int m = 0; m < MT; m++) {
                s[2 * m]     = bfr(bfr(odd ? sc[m][1] : sc[m][0]) * SCALE);
                s[2 * m + 1] = bfr(bfr(odd ? sc[m][3] : sc[m][2]) * SCALE);
                mx = fmaxf(mx, fmaxf(s[2 * m], s[2 * m + 1]));
            }
            mx = warp_max(valid ? mx : -INFINITY);
            const float mref = (mx == -INFINITY) ? 0.f : mx;
            float l = 0.f;
            uint32_t pb[2 * MT];
#pragma unroll
            for (int i = 0; i < 2 * MT; i++) {
                const float e = valid ? ex2((s[i] - mref) * LOG2E) : 0.f;
                l += e;
                pb[i] = pack_bf16(e, 0.f) << (odd * 16);
            }
            l = warp_sum(l);
            st_pkt_if(lane == 0, &g_ml[it0], __float_as_uint(mx), __float_as_uint(l), tag, 0u);
            float acc[8][4];
#pragma unroll
            for (int i = 0; i < 8; i++) { acc[i][0] = acc[i][1] = acc[i][2] = acc[i][3] = 0.f; }
            mbar_wait(bar_full + (u0 + 2) * 8, ph);
            mbar_wait(bar_full + (u0 + 3) * 8, ph);
            {
                const uint32_t so = (u0 + 2) * UNIT;
#pragma unroll
                for (int m = 0; m < MT; m++) {
#pragma unroll
                    for (int i = 0; i < 8; i++) {
                        uint32_t a[4];
                        ldsm4t(a, offV[i & 3] + so + m * 4096 + (i >> 2) * 128);
                        mma16816(acc[i], a, pb[2 * m], pb[2 * m + 1]);
                    }
                }
            }
            __syncwarp();
            if (lane == 0) mbar_arrive(bar_empty + ((u0 >> 1) + 1) * 8);
            float T[16];
#pragma unroll
            for (int i = 0; i < 8; i++) { T[2 * i] = acc[i][0] + acc[i][3]; T[2 * i + 1] = acc[i][2] + acc[i][1]; }
            float U[16];
#pragma unroll
            for (int c = 0; c < 16; c++) if (!(c & 2)) U[c] = T[c] + __shfl_xor_sync(0xffffffffu, T[c ^ 2], 1);
            const float y0 = U[0] + __shfl_xor_sync(0xffffffffu, U[4], 2), y1 = U[1] + __shfl_xor_sync(0xffffffffu, U[5], 2);
            const float y2 = U[8] + __shfl_xor_sync(0xffffffffu, U[12], 2), y3 = U[9] + __shfl_xor_sync(0xffffffffu, U[13], 2);
            st_f4_if(1u, g_op + (size_t)it0 * 32 + t * 8 + g, y0, y1, y2, y3, tag);
        }
        if (cta >= NFF) return;
    } else if (warp == 1) {
        if (lane == 0) {
            asm volatile("prefetch.tensormap [%0];" ::"l"(&tm_o) : "memory");
            asm volatile("prefetch.tensormap [%0];" ::"l"(&tm_gate) : "memory");
            asm volatile("prefetch.tensormap [%0];" ::"l"(&tm_up) : "memory");
            asm volatile("prefetch.tensormap [%0];" ::"l"(&tm_dn) : "memory");
        }
        uint32_t item = cta, pend = 0, u = (K_WKV < 4 ? K_WKV : 4);
        auto claim = [&]() {
            asm volatile("{\n.reg .pred p;\nsetp.eq.u32 p, %2, 0;\n@p atom.relaxed.gpu.global.add.u32 %0, [%1], 1;\n}" : "+r"(pend) : "l"(&g_ctr_item + lane), "r"(lane) : "memory");
        };
        if (u > K_CLAIM) claim();
        for (;; u++) {
            if (u >= K_WKV) mbar_wait(bar_full + ((u - K_WKV) & 7) * 8, ((u - K_WKV) >> 3) & 1);
            if (!(u & 1) && u >= 2 * NS) mbar_wait(bar_empty + ((u >> 1) & 3) * 8, ((u >> 3) - 1) & 1);
            if ((u & 3) == 0) {
                item = __shfl_sync(0xffffffffu, pend, 0) % NITEMS + GRID;
                if (item >= (uint32_t)NITEMS) break;
            }
            if (lane == 0) issue_unit(u, item);
            if ((u & 3) == K_CLAIM) claim();
            __syncwarp();
        }
        if (lane == 0) {
            s_misc[2 + ((u >> 2) & 1)] = NITEMS;
            s_misc[1] = (int)((u >> 1) & 3);
            mbar_arrive(bar_full + (u & 7) * 8);
            TS(2);
        }
        __syncwarp();
        bar_arrive<BAR_GO, 288>();
        const int slot0 = (u >> 1) & 3, opr = oproj_role(cta);
        const int box0 = opr >= 0 ? 0 : 2, nbox = cta < NFF ? NBOX : 2;
        const int win = (int)(item - NITEMS) < K_R0 ? K_WIN : K_WIN2;
#pragma unroll
        for (int i = 0; i < NBOX; i++) {
            const int pc = (i - 2) >> 1;
            if (i >= box0 && i < nbox) {
                if (i >= 4 && i < BOX_DN && !(i & 1)) mbar_wait(bar_empty + ((slot0 + pc) & 3) * 8, ((u + 2 * pc) / 8 - 1) & 1);
                if (i >= box0 + win) mbar_wait(bar_box + (i - win) * 8, 0);
                if (i - box0 < K_HOLD) { const uint32_t w = u + (i - box0) - K_HOLD; mbar_wait(bar_full + (w & 7) * 8, (w >> 3) & 1); }
                if (lane == 0) {
                    const uint32_t bar = bar_box + i * 8;
                    if (i < 2) {
                        mbar_expect_tx(bar, 16 * WROW);
                        const int r0 = (opr >> 2) * DH + (opr & 3) * 16 + i * 64;
                        tensor_load_3d(sb + OFF_WO + i * 16 * WROW, &tm_o, r0, bar, pol);
                        tensor_load_3d(sb + OFF_WO + (i * 16 + 8) * WROW, &tm_o, r0 + 8, bar, pol);
                    } else if (i < BOX_DN) {
                        mbar_expect_tx(bar, GU_BOX);
                        tensor_load_2d(sb + OFF_RING + ((slot0 + pc) & 3) * SLOT + (i & 1) * GU_BOX, (i & 1) ? &tm_up : &tm_gate, cta * FC - (cta & 1) * 8, pc * GU_ROWS, bar);
                    } else {
                        const int r0 = (i - BOX_DN) * 16;
                        mbar_expect_tx(bar, (i < BOX_DN + 2 ? 16 : 8) * WROW);
                        tensor_load_3d(sb + OFF_DN + r0 * WROW, &tm_dn, cta * FC + r0, bar, pol);
                        if (i < BOX_DN + 2) tensor_load_3d(sb + OFF_DN + (r0 + 8) * WROW, &tm_dn, cta * FC + r0 + 8, bar, pol);
                    }
                }
                __syncwarp();
            }
        }
        return;
    }

    const int vw = (warp == 0) ? 8 : warp - 2, wt = tid - 64;
    if (vw >= 4 && vw < 8 && cta < NOP) {
        const int w2 = vw - 4;
        float4 xv[5];
#pragma unroll
        for (int j = 0; j < 5; j++) {
            const uint2 u = reinterpret_cast<const uint2*>(s_x + w2 * DM)[(j < 4 || lane < 16) ? lane + 32 * j : lane];
            xv[j] = make_float4(bf_lo(u.x), bf_hi(u.x), bf_lo(u.y), bf_hi(u.y));
        }
        const float2 st = ln_stats(xv, lane);
#pragma unroll
        for (int j = 0; j < 5; j++) {
            uint2 o;
            o.x = pack_bf16(bfr(xv[j].x - st.x) * st.y, bfr(xv[j].y - st.x) * st.y);
            o.y = pack_bf16(bfr(xv[j].z - st.x) * st.y, bfr(xv[j].w - st.x) * st.y);
            if (j < 4 || lane < 16) *reinterpret_cast<uint2*>(smem + OFF_XN + w2 * WPITCH + (lane + 32 * j) * 8) = o;
        }
        bar_sync<BAR_Q, 128>();
        if (w2 < 2) {
            float c[4][4];
#pragma unroll
            for (int i = 0; i < 4; i++) { c[i][0] = c[i][1] = c[i][2] = c[i][3] = 0.f; }
            const uint32_t bbase = sb + OFF_XN + (rr & 3) * WPITCH + id * 16;
            const uint32_t abase = sb + OFF_WO + ((id >> 1) * 8 + rr) * 64 + (((2 * w2 + (id & 1)) ^ (rr >> 1)) << 4);
#pragma unroll 1
            for (int bx = 0; bx < 3; bx++) {
                mbar_wait(bar_wq + bx * 8, 0);
#pragma unroll
                for (int k2 = 0; k2 < 6; k2++) {
                    uint32_t bf[4], a0[4], a1[4];
                    ldsm4(bf, bbase + (bx * 6 + k2) * 64);
                    ldsm4t(a0, abase + (bx * 6 + k2) * 2048);
                    ldsm4t(a1, abase + (bx * 6 + k2) * 2048 + 1024);
                    mma16816(c[(2 * k2) & 3], a0, bf[0], bf[1]);
                    mma16816(c[(2 * k2 + 1) & 3], a1, bf[2], bf[3]);
                }
            }
            if (wt == 128) TS(24);
            const bool od = g & 1;
            const float v0 = (c[0][0] + c[1][0]) + (c[2][0] + c[3][0]), v1 = (c[0][1] + c[1][1]) + (c[2][1] + c[3][1]);
            const float v2 = (c[0][2] + c[1][2]) + (c[2][2] + c[3][2]), v3 = (c[0][3] + c[1][3]) + (c[2][3] + c[3][3]);
            const float r0 = __shfl_xor_sync(0xffffffffu, od ? v0 : v1, 4), r1 = __shfl_xor_sync(0xffffffffu, od ? v2 : v3, 4);
            if (t < 2) {
                uint2* q = g_q + ((2 * t + (g & 1)) * NH + (cta >> 2)) * (DH / 2) + (cta & 3) * 16 + w2 * 8 + (g >> 1);
                st_pkt8(q, od ? pack_bf16(r0, v1) : pack_bf16(v0, r0), tag);
                st_pkt8(q + 4, od ? pack_bf16(r1, v3) : pack_bf16(v2, r1), tag);
            }
            if (wt == 128) TS(26);
        }
    }
    float* s_comb = reinterpret_cast<float*>(smem + OFF_COMB);
    float* s_red = reinterpret_cast<float*>(smem + OFF_RED);
#pragma unroll 1
    for (uint32_t pass = (vw == 8) ? 1u : 0u; pass < 2; pass++) {
        uint32_t real;
        asm volatile("mov.u32 %0, %1;" : "=r"(real) : "r"(pass));
        int lane, rank;
        asm volatile("mov.u32 %0, %laneid;" : "=r"(lane));
        asm volatile("mov.u32 %0, %ctaid.x;" : "=r"(rank));
        const int g = lane >> 2, t = lane & 3, id = lane >> 3, rr = lane & 7;
        const bool lead = real && wt == 0;
        if (vw < 8) {
            if (real) {
                const int o = oproj_role(rank);
                for (int n = wt; n < DM; n += 256) {
                    st_pkt_if(o >= 0, g_p1 + o * DM + n, 0u, 0u, 0u, 0u);
                    st_pkt_if(rank < NFF, g_p2 + rank * DM + n, 0u, 0u, 0u, 0u);
                }
                if (vw == 0) {
#pragma unroll
                    for (int r = 0; r < (HREP + 3) / 4; r++)
                        st_pkt_if(4 * r + t < HREP && rank < NRED, g_h + ((4 * r + t) * NB + (rank & 1) * 2 + (lane >> 4)) * (DM / 4) + (rank >> 1) * 4 + (g & 3), 0u, 0u, 0u, 0u);
                }
                bar_sync<BAR_GO, 288>();
            } else bar_sync<BAR_W, 256>();
        }
        if (vw < 8) {
            if (lead) TS(8);
            const int opr = oproj_role(rank);
            if (opr >= 0) {
            constexpr int PW = IPH / 2;
            constexpr int NML = IPH / 32, NOV = PW / 4;
            const int half = vw & 1;
            const int base = ((vw >> 1) * NH + (opr >> 2)) * IPH;
            uint4 pk[NML + NOV];
            {
                uint32_t need[NML + NOV];
#pragma unroll
                for (int i = 0; i < NML + NOV; i++) need[i] = real;
                const uint4* pml = g_ml + base + lane;
                const uint4* pov = g_op + (size_t)(base + half * PW + id) * 32 + (opr & 3) * 8 + rr;
                poll_pkts<NML + NOV, NML>(pk, need, tag, [&](int i) { return i < NML ? pml + i * 32 : pov + (i - NML) * 128; });
            }
            if (real && wt == 224) TS(27);
            float M = __uint_as_float(pk[0].x);
#pragma unroll
            for (int i = 1; i < NML; i++) M = fmaxf(M, __uint_as_float(pk[i].x));
            M = warp_max(M);
            float wgt[NML], L = 0.f;
#pragma unroll
            for (int i = 0; i < NML; i++) { wgt[i] = ex2((__uint_as_float(pk[i].x) - M) * 1.4426950408889634f); L += wgt[i] * __uint_as_float(pk[i].y); }
            float4 a = make_float4(0.f, 0.f, 0.f, 0.f);
#pragma unroll
            for (int i = 0; i < NOV; i++) {
                const int j = i * 4;
                const float wsel = half ? wgt[(PW + j) / 32] : wgt[j / 32];
                const float w = __shfl_sync(0xffffffffu, wsel, ((half * PW + j) & 31) + id);
                const float4 o4 = unpack_f4(pk[NML + i]);
                a.x = fmaf(w, o4.x, a.x); a.y = fmaf(w, o4.y, a.y); a.z = fmaf(w, o4.z, a.z); a.w = fmaf(w, o4.w, a.w);
            }
            L = warp_sum(L);
#pragma unroll
            for (int o = 8; o <= 16; o <<= 1) {
                a.x += __shfl_xor_sync(0xffffffffu, a.x, o); a.y += __shfl_xor_sync(0xffffffffu, a.y, o);
                a.z += __shfl_xor_sync(0xffffffffu, a.z, o); a.w += __shfl_xor_sync(0xffffffffu, a.w, o);
            }
            const float inv = __fdividef(1.0f, L);
            if (lane < 8) reinterpret_cast<float4*>(s_comb + vw * 32)[lane] = make_float4(a.x * inv, a.y * inv, a.z * inv, a.w * inv);
            if (vw < 6) {
                uint32_t wa[6][2][4];
                if (real) { mbar_wait(bar_box, 0); mbar_wait(bar_box + 8, 0); }
#pragma unroll
                for (int i = 0; i < 6; i++) {
                    const int mt = vw + 6 * i;
                    const uint32_t ad = sb + OFF_WO + ((id >> 1) * 8 + rr) * WROW + (mt >> 2) * 128 + ((((mt & 3) * 2 + (id & 1)) ^ ((rr + (mt >> 2)) & 7)) << 4);
                    ldsm4t(wa[i][0], ad);
                    ldsm4t(wa[i][1], ad + 16 * WROW);
                }
                if (real) bar_sync<BAR_C, 256>();
                if (lead) TS(9);
                const float4* c0 = reinterpret_cast<const float4*>(s_comb + (g & 3) * 64) + 2 * t;
                const float4 u0 = c0[0], u1 = c0[1], v0 = c0[8], v1 = c0[9];
                const uint32_t bo0 = pack_bf16(u0.x + v0.x, u1.x + v1.x), bo1 = pack_bf16(u0.y + v0.y, u1.y + v1.y);
                const uint32_t bo2 = pack_bf16(u0.z + v0.z, u1.z + v1.z), bo3 = pack_bf16(u0.w + v0.w, u1.w + v1.w);
                float c[6][4];
#pragma unroll
                for (int i = 0; i < 6; i++) { c[i][0] = c[i][1] = c[i][2] = c[i][3] = 0.f; mma16816(c[i], wa[i][0], bo0, bo1); }
#pragma unroll
                for (int i = 0; i < 6; i++) mma16816(c[i], wa[i][1], bo2, bo3);
#pragma unroll
                for (int i = 0; i < 6; i++) send_tile(real, g_p1 + opr * DM + (vw + 6 * i) * 16, c[i], g, t, tag);
            } else {
                __syncwarp();
                if (real) bar_arrive<BAR_C, 256>();
            }
            }
            if (lead) TS(11);
            if (rank >= NFF) continue;
            if (rank < NRED) {
                reduce_cols<NOP>(real, g_p1 + rank * 8, s_red, vw, lane, tag);
                if (real) bar_sync<BAR_W, 256>();
                if (lead) TS(12);
                if (vw == 0) {
                    const int ob = (rank & 1) * 2 + (lane >> 4), oc = (rank >> 1) * 16 + (lane & 15);
                    const float a1 = sum8(s_red + rr * 4 + (id & 1) * 2 + (id >> 1));
                    const float h = __bfloat162float(s_x[ob * DM + oc]) + bfr(a1);
                    const uint32_t u = pack_bf16(h, __shfl_down_sync(0xffffffffu, h, 1));
                    const uint32_t u0 = __shfl_sync(0xffffffffu, u, lane & ~3), u2 = __shfl_sync(0xffffffffu, u, (lane & ~3) + 2);
#pragma unroll
                    for (int r = 0; r < (HREP + 3) / 4; r++)
                        st_pkt_if(4 * r + t < HREP ? real : 0u, g_h + ((4 * r + t) * NB + ob) * (DM / 4) + (oc >> 2), u0, u2, tag, 0u);
                }
            }
        }
        if (vw < 4 || vw == 8) {
            const int ct = (vw == 8) ? 4 : vw;
            constexpr int KS = GU_ROWS / 16;
            constexpr int NPRE = 32;
            uint32_t ga[NPRE][4];
            uint32_t alast = 0;
            const uint32_t aoff = sb + OFF_RING + (id & 1) * GU_BOX + ((id >> 1) * 8 + rr) * (GW * 2) + ct * 16 + (rank & 1) * 16;
            int sl = s_misc[1];
#pragma unroll
            for (int pc = 0; pc < GU_PIECES; pc++) {
                if (real) { mbar_wait(bar_box + (2 + 2 * pc) * 8, 0); mbar_wait(bar_box + (3 + 2 * pc) * 8, 0); }
                alast = aoff + sl * SLOT;
#pragma unroll
                for (int k = 0; k < KS; k++) if (pc * KS + k < NPRE) ldsm4t(ga[pc * KS + k], alast + k * 16 * GW * 2);
                sl = (sl + 1) & 3;
            }
            float cs[2][4] = {{0.f, 0.f, 0.f, 0.f}, {0.f, 0.f, 0.f, 0.f}};
#pragma unroll
            for (int k = 0; k < DM / 16; k++) {
                if (k < NPRE) mma16816(cs[k & 1], ga[k < NPRE ? k : 0], 0x3f803f80u, 0x3f803f80u);
                else { uint32_t al[4]; ldsm4t(al, alast + (k - (GU_PIECES - 1) * KS) * 16 * GW * 2); mma16816(cs[k & 1], al, 0x3f803f80u, 0x3f803f80u); }
            }
            const float csg = cs[0][0] + cs[1][0], csu = cs[0][2] + cs[1][2];
            if (lead) TS(10);
            if (real) bar_sync<BAR_XN, 288>();
            if (lead) TS(14);
            float cc[4][4];
#pragma unroll
            for (int i = 0; i < 4; i++) { cc[i][0] = cc[i][1] = cc[i][2] = cc[i][3] = 0.f; }
            const uint32_t bbase = sb + OFF_XN + (rr & 3) * WPITCH + (rr >> 2) * 64 + id * 16;
#pragma unroll
            for (int k4 = 0; k4 < DM / 64; k4++) {
                uint32_t bf[4];
                ldsm4(bf, bbase + k4 * 128);
#pragma unroll
                for (int j = 0; j < 4; j++) {
                    const int k = 4 * k4 + j;
                    if (k < NPRE) mma16816(cc[j], ga[k < NPRE ? k : 0], bf[2 * (j & 1)], bf[2 * (j & 1) + 1]);
                    else { uint32_t al[4]; ldsm4t(al, alast + (k - (GU_PIECES - 1) * KS) * 16 * GW * 2); mma16816(cc[j], al, bf[2 * (j & 1)], bf[2 * (j & 1) + 1]); }
                }
            }
            float c[4];
#pragma unroll
            for (int e = 0; e < 4; e++) c[e] = (cc[0][e] + cc[1][e]) + __shfl_xor_sync(0xffffffffu, cc[2][e] + cc[3][e], 2);
            if (real) bar_sync<BAR_ST, 288>();
            if (t < 2) {
                __nv_bfloat16* s_act = reinterpret_cast<__nv_bfloat16*>(smem + OFF_ACT);
                const float4 st4 = reinterpret_cast<const float4*>(s_comb + 256)[t];
#pragma unroll
                for (int e = 0; e < 2; e++) {
                    const float mb = e ? st4.z : st4.x, rs = e ? st4.w : st4.y;
                    const float gg = bfr((c[e] - mb * csg) * rs), uu = bfr((c[2 + e] - mb * csu) * rs);
                    const float ge = bfr(__fdividef(gg, 1.0f + ex2(gg * fmaf(gg * gg, -0.10294324f, -2.3022082f))));
                    s_act[(2 * t + e) * (ACT_PITCH / 2) + ct * 8 + g] = __float2bfloat16_rn(ge * uu);
                }
            }
            __syncwarp();
            if (real) bar_arrive<BAR_ACT, 288>();
            if (lead) TS(15);
            if (vw == 8) return;
        } else {
            const int lw = vw - 4;
            uint4 hp[5];
            uint32_t need[5];
#pragma unroll
            for (int j = 0; j < 5; j++) need[j] = (j < 4 || lane < 16) ? real : 0u;
            poll_pkts<5, 5>(hp, need, tag, [&](int j) { return g_h + ((rank % HREP) * NB + lw) * (DM / 4) + lane + 32 * j; });
#pragma unroll
            for (int j = 0; j < 5; j++)
                if (j < 4 || lane < 16) *reinterpret_cast<uint2*>(smem + OFF_XN + lw * WPITCH + (lane + 32 * j) * 8) = make_uint2(hp[j].x, hp[j].y);
            __syncwarp();
            if (real) bar_arrive<BAR_XN, 288>();
            if (real && wt == 128) TS(13);
            float4 hv[5];
#pragma unroll
            for (int j = 0; j < 5; j++) hv[j] = make_float4(bf_lo(hp[j].x), bf_hi(hp[j].x), bf_lo(hp[j].y), bf_hi(hp[j].y));
            const float2 st = ln_stats(hv, lane);
            if (lane == 0) reinterpret_cast<float2*>(s_comb + 256)[lw] = st;
            __syncwarp();
            if (real) bar_arrive<BAR_ST, 288>();
#pragma unroll
            for (int j = 0; j < 5; j++) if (real && (j < 4 || lane < 16)) reinterpret_cast<uint2*>(s_x + lw * DM)[lane + 32 * j] = make_uint2(hp[j].x, hp[j].y);
            uint32_t da[9][2][4];
            if (real) { mbar_wait(bar_box + BOX_DN * 8, 0); mbar_wait(bar_box + (BOX_DN + 1) * 8, 0); }
            const int jc = lw * 2 + (id & 1);
#pragma unroll
            for (int i = 0; i < 9; i++) {
                const uint32_t ad = sb + OFF_DN + ((id >> 1) * 8 + rr) * WROW + i * 128 + ((jc ^ ((rr + i) & 7)) << 4);
                ldsm4t(da[i][0], ad);
                ldsm4t(da[i][1], ad + 16 * WROW);
            }
            if (real) bar_sync<BAR_ACT, 288>();
            if (real && wt == 128) TS(16);
            uint32_t ba[5];
            const uint32_t* s_act32 = reinterpret_cast<const uint32_t*>(smem + OFF_ACT + (g & 3) * ACT_PITCH);
#pragma unroll
            for (int k = 0; k < 5; k++) ba[k] = s_act32[k * 4 + t];
            float c[9][4];
#pragma unroll
            for (int i = 0; i < 9; i++) { c[i][0] = c[i][1] = c[i][2] = c[i][3] = 0.f; mma16816(c[i], da[i][0], ba[0], ba[1]); }
#pragma unroll
            for (int i = 0; i < 9; i++) mma16816(c[i], da[i][1], ba[2], ba[3]);
            if (real) mbar_wait(bar_box + (BOX_DN + 2) * 8, 0);
            if (real && wt == 128) TS(17);
#pragma unroll
            for (int i = 0; i < 9; i += 2) {
                const int ci = (i + 1 < 9) ? i + (id >> 1) : i;
                uint32_t a2[4];
                ldsm4t(a2, sb + OFF_DN + (32 + rr) * WROW + ci * 128 + ((jc ^ ((rr + ci) & 7)) << 4));
                mma1688(c[i], a2[0], a2[1], ba[4]);
                if (i + 1 < 9) mma1688(c[i + 1], a2[2], a2[3], ba[4]);
            }
#pragma unroll
            for (int i = 0; i < 9; i++) send_tile(real, g_p2 + rank * DM + (lw + 4 * i) * 16, c[i], g, t, tag);
            if (real && wt == 128) TS(18);
        }
        if (rank < NRED) {
            reduce_cols<NFF>(real, g_p2 + rank * 8, s_red, vw, lane, tag);
            if (real) bar_sync<BAR_W, 256>();
            if (lead) TS(19);
            if (vw == 0) {
                const int ob = (rank & 1) * 2 + (lane >> 4), oc = (rank >> 1) * 16 + (lane & 15);
                const float a = sum8(s_red + rr * 4 + (id & 1) * 2 + (id >> 1));
                if (real) p.out[ob * DM + oc] = __float2bfloat16_rn(__bfloat162float(s_x[ob * DM + oc]) + bfr(a));
                if (lead) TS(20);
            }
        }
    }
}

typedef CUresult (*EncodeTiledFn)(CUtensorMap*, CUtensorMapDataType, cuuint32_t, void*, const cuuint64_t*, const cuuint64_t*,
                                  const cuuint32_t*, const cuuint32_t*, CUtensorMapInterleave, CUtensorMapSwizzle,
                                  CUtensorMapL2promotion, CUtensorMapFloatOOBfill);

}

extern "C" void kernel_launch(void* const* d_in, const int* in_sizes, int n_in, void* d_out, int out_size) {
    (void)in_sizes; (void)n_in; (void)out_size;
    static EncodeTiledFn encode = nullptr;
    if (!encode) {
        void* fn = nullptr;
        cudaDriverEntryPointQueryResult qr;
        cudaGetDriverEntryPoint("cuTensorMapEncodeTiled", &fn, cudaEnableDefault, &qr);
        encode = (EncodeTiledFn)fn;
        cudaFuncSetAttribute(fused_decode_kernel, cudaFuncAttributeMaxDynamicSharedMemorySize, SMEM_BYTES);
    }
    CUtensorMap tmq, tmo, tmg, tmu, tmd;
    const cuuint32_t estr[3] = {1, 1, 1};
    {
        const cuuint64_t gdim[2] = {(cuuint64_t)(NH * DH), (cuuint64_t)DM};
        const cuuint64_t gstr[1] = {(cuuint64_t)(NH * DH) * 2};
        const cuuint32_t box[2] = {32, 192};
        encode(&tmq, CU_TENSOR_MAP_DATA_TYPE_BFLOAT16, 2, d_in[3], gdim, gstr, box, estr, CU_TENSOR_MAP_INTERLEAVE_NONE,
               CU_TENSOR_MAP_SWIZZLE_64B, CU_TENSOR_MAP_L2_PROMOTION_L2_256B, CU_TENSOR_MAP_FLOAT_OOB_FILL_NONE);
    }
    {
        const cuuint64_t gdim[2] = {(cuuint64_t)DF, (cuuint64_t)DM};
        const cuuint64_t gstr[1] = {(cuuint64_t)DF * 2};
        const cuuint32_t box[2] = {(cuuint32_t)GW, (cuuint32_t)GU_ROWS};
        encode(&tmg, CU_TENSOR_MAP_DATA_TYPE_BFLOAT16, 2, d_in[6], gdim, gstr, box, estr, CU_TENSOR_MAP_INTERLEAVE_NONE,
               CU_TENSOR_MAP_SWIZZLE_NONE, CU_TENSOR_MAP_L2_PROMOTION_L2_128B, CU_TENSOR_MAP_FLOAT_OOB_FILL_NONE);
        encode(&tmu, CU_TENSOR_MAP_DATA_TYPE_BFLOAT16, 2, d_in[7], gdim, gstr, box, estr, CU_TENSOR_MAP_INTERLEAVE_NONE,
               CU_TENSOR_MAP_SWIZZLE_NONE, CU_TENSOR_MAP_L2_PROMOTION_L2_128B, CU_TENSOR_MAP_FLOAT_OOB_FILL_NONE);
    }
    {
        const cuuint64_t gstr[2] = {128, (cuuint64_t)WROW};
        const cuuint64_t gdo[3] = {64, 9, (cuuint64_t)(NH * DH)}, gdd[3] = {64, 9, (cuuint64_t)DF};
        const cuuint32_t box[3] = {64, 9, 8};
        encode(&tmo, CU_TENSOR_MAP_DATA_TYPE_BFLOAT16, 3, d_in[4], gdo, gstr, box, estr, CU_TENSOR_MAP_INTERLEAVE_NONE,
               CU_TENSOR_MAP_SWIZZLE_128B, CU_TENSOR_MAP_L2_PROMOTION_L2_128B, CU_TENSOR_MAP_FLOAT_OOB_FILL_NONE);
        encode(&tmd, CU_TENSOR_MAP_DATA_TYPE_BFLOAT16, 3, d_in[8], gdd, gstr, box, estr, CU_TENSOR_MAP_INTERLEAVE_NONE,
               CU_TENSOR_MAP_SWIZZLE_128B, CU_TENSOR_MAP_L2_PROMOTION_L2_128B, CU_TENSOR_MAP_FLOAT_OOB_FILL_NONE);
    }
    Params p;
    p.x = (const __nv_bfloat16*)d_in[0];
    p.k = (const char*)d_in[1];
    p.v = (const char*)d_in[2];
    p.out = (__nv_bfloat16*)d_out;
    fused_decode_kernel<<<GRID, NTHR, SMEM_BYTES, cudaStreamPerThread>>>(p, tmq, tmo, tmg, tmu, tmd);
}
```

```cpp
#include <cuda_runtime.h>
#include <cuda_bf16.h>
#include <cuda.h>
#include <stdint.h>

namespace {

constexpr int K_WKV   = 4;
constexpr int K_CLAIM = 2;
constexpr int K_HOLD  = 2;
constexpr int K_WIN   = 2;
constexpr int K_WIN2  = 3;
constexpr int K_J     = 4;
static_assert(K_WKV == 4 && K_CLAIM < 4, "start-up issues the first item");

constexpr int NB = 4, DM = 576, NH = 32, SK = 8192, DH = 128, DF = 4608;
constexpr int KEYS   = 128;
constexpr int IPH    = SK / KEYS;
constexpr int NITEMS = NB * NH * IPH;
constexpr int NS     = 4;
constexpr int UNIT   = 16384;
constexpr int SLOT   = KEYS * DH * 2;
constexpr int MT     = KEYS / 16;
constexpr int NTHR   = 320;
constexpr int GRID   = 132;
constexpr int NOP    = 128;
constexpr int FC     = 40;
constexpr int NFF    = (DF + FC - 1) / FC;
constexpr int NRED   = DM / 8;
constexpr int HREP   = 4;
constexpr int WPITCH = DM * 2 + 16;
constexpr int GW     = 48;
constexpr int GU_ROWS = 144;
constexpr int GU_BOX = GU_ROWS * GW * 2;
constexpr int GU_PIECES = DM / GU_ROWS;
static_assert(2 * GU_BOX <= SLOT && GU_PIECES <= NS && SLOT == 2 * UNIT, "gate/up pieces");

constexpr int WROW     = DM * 2;
constexpr int OFF_RING = 0;
constexpr int OFF_WO   = OFF_RING + NS * SLOT;
constexpr int OFF_DN   = OFF_WO + 32 * WROW;
constexpr int OFF_XN   = OFF_DN + FC * WROW;
constexpr int OFF_X    = OFF_XN + 4 * WPITCH;
constexpr int OFF_Q    = OFF_X + NB * DM * 2;
constexpr int OFF_COMB = OFF_Q + 2 * 512;
constexpr int OFF_RED  = OFF_COMB + 8 * 32 * 4 + 32;
constexpr int OFF_ACT  = OFF_RED + 8 * 32 * 4;
constexpr int ACT_PITCH = 112;
constexpr int OFF_BAR  = OFF_ACT + 4 * ACT_PITCH;
constexpr int BOX_DN   = 2 + 2 * GU_PIECES;
constexpr int NBOX     = BOX_DN + 3;
constexpr int OFF_MISC = OFF_BAR + (3 * NS + 3 + NBOX) * 8;
constexpr int SMEM_BYTES = OFF_MISC + 64;
static_assert(OFF_WO % 1024 == 0 && OFF_DN % 1024 == 0 && DM * 64 <= 32 * WROW, "staging");
static_assert(OFF_BAR % 8 == 0 && OFF_COMB % 16 == 0 && OFF_RED % 16 == 0, "align");
static_assert(SMEM_BYTES <= 232448, "smem");

__device__ unsigned int g_ctr_item;
__device__ __align__(128) uint2 g_q[NB * NH * DH / 2];
__device__ __align__(128) uint4 g_ml[NITEMS];
__device__ __align__(128) uint4 g_op[NITEMS * 32];
__device__ __align__(128) uint4 g_p1[NOP * DM];
__device__ __align__(128) uint4 g_h[HREP * NB * DM / 4];
__device__ __align__(128) uint4 g_p2[NFF * DM];

__device__ __forceinline__ uint32_t smem_u32(const void* p) { return (uint32_t)__cvta_generic_to_shared(p); }
__device__ __forceinline__ void mbar_init(uint32_t bar, uint32_t cnt) { asm volatile("mbarrier.init.shared::cta.b64 [%0], %1;" ::"r"(bar), "r"(cnt) : "memory"); }
__device__ __forceinline__ void mbar_expect_tx(uint32_t bar, uint32_t bytes) { asm volatile("mbarrier.arrive.expect_tx.shared::cta.b64 _, [%0], %1;" ::"r"(bar), "r"(bytes) : "memory"); }
__device__ __forceinline__ void mbar_arrive(uint32_t bar) { asm volatile("mbarrier.arrive.shared::cta.b64 _, [%0];" ::"r"(bar) : "memory"); }
__device__ __forceinline__ bool mbar_try(uint32_t bar, uint32_t parity) {
    uint32_t ok;
    asm volatile("{\n.reg .pred p;\nmbarrier.try_wait.parity.shared::cta.b64 p, [%1], %2;\nselp.u32 %0, 1, 0, p;\n}" : "=r"(ok) : "r"(bar), "r"(parity) : "memory");
    return ok != 0;
}
__device__ __forceinline__ void mbar_wait(uint32_t bar, uint32_t parity) {
    uint32_t n = 0;
    while (!mbar_try(bar, parity)) { if (++n > (1u << 24)) __trap(); }
}
__device__ __forceinline__ void bulk_load(uint32_t dst, const void* src, uint32_t bytes, uint32_t bar, uint64_t pol) {
    asm volatile("cp.async.bulk.shared::cluster.global.mbarrier::complete_tx::bytes.L2::cache_hint [%0], [%1], %2, [%3], %4;"
                 ::"r"(dst), "l"(src), "r"(bytes), "r"(bar), "l"(pol) : "memory");
}
__device__ __forceinline__ void bulk_load_plain(uint32_t dst, const void* src, uint32_t bytes, uint32_t bar) {
    asm volatile("cp.async.bulk.shared::cluster.global.mbarrier::complete_tx::bytes [%0], [%1], %2, [%3];"
                 ::"r"(dst), "l"(src), "r"(bytes), "r"(bar) : "memory");
}
__device__ __forceinline__ void tensor_load_2d(uint32_t dst, const CUtensorMap* tm, int c0, int c1, uint32_t bar) {
    asm volatile("cp.async.bulk.tensor.2d.shared::cluster.global.mbarrier::complete_tx::bytes [%0], [%1, {%3, %4}], [%2];"
                 ::"r"(dst), "l"(tm), "r"(bar), "r"(c0), "r"(c1) : "memory");
}
__device__ __forceinline__ void tensor_load_3d(uint32_t dst, const CUtensorMap* tm, int row, uint32_t bar, uint64_t pol) {
    asm volatile("cp.async.bulk.tensor.3d.shared::cluster.global.mbarrier::complete_tx::bytes.L2::cache_hint [%0], [%1, {%3, %3, %4}], [%2], %5;"
                 ::"r"(dst), "l"(tm), "r"(bar), "r"(0), "r"(row), "l"(pol) : "memory");
}
__device__ __forceinline__ void ldsm4(uint32_t (&r)[4], uint32_t addr) {
    asm volatile("ldmatrix.sync.aligned.m8n8.x4.shared.b16 {%0,%1,%2,%3}, [%4];" : "=r"(r[0]), "=r"(r[1]), "=r"(r[2]), "=r"(r[3]) : "r"(addr) : "memory");
}
__device__ __forceinline__ void ldsm4t(uint32_t (&r)[4], uint32_t addr) {
    asm volatile("ldmatrix.sync.aligned.m8n8.x4.trans.shared.b16 {%0,%1,%2,%3}, [%4];" : "=r"(r[0]), "=r"(r[1]), "=r"(r[2]), "=r"(r[3]) : "r"(addr) : "memory");
}
__device__ __forceinline__ void mma16816(float (&c)[4], const uint32_t (&a)[4], uint32_t b0, uint32_t b1) {
    asm volatile("mma.sync.aligned.m16n8k16.row.col.f32.bf16.bf16.f32 {%0,%1,%2,%3}, {%4,%5,%6,%7}, {%8,%9}, {%0,%1,%2,%3};"
                 : "+f"(c[0]), "+f"(c[1]), "+f"(c[2]), "+f"(c[3]) : "r"(a[0]), "r"(a[1]), "r"(a[2]), "r"(a[3]), "r"(b0), "r"(b1));
}
__device__ __forceinline__ void mma1688(float (&c)[4], uint32_t a0, uint32_t a1, uint32_t b0) {
    asm volatile("mma.sync.aligned.m16n8k8.row.col.f32.bf16.bf16.f32 {%0,%1,%2,%3}, {%4,%5}, {%6}, {%0,%1,%2,%3};"
                 : "+f"(c[0]), "+f"(c[1]), "+f"(c[2]), "+f"(c[3]) : "r"(a0), "r"(a1), "r"(b0));
}
__device__ __forceinline__ float bfr(float x) { return __bfloat162float(__float2bfloat16_rn(x)); }
__device__ __forceinline__ uint32_t pack_bf16(float lo, float hi) {
    uint32_t r; asm("cvt.rn.bf16x2.f32 %0, %1, %2;" : "=r"(r) : "f"(hi), "f"(lo)); return r;
}
__device__ __forceinline__ uint32_t max_bf16x2(uint32_t a, uint32_t b) { uint32_t r; asm("max.bf16x2 %0, %1, %2;" : "=r"(r) : "r"(a), "r"(b)); return r; }
__device__ __forceinline__ float bf_lo(uint32_t u) { return __uint_as_float(u << 16); }
__device__ __forceinline__ float bf_hi(uint32_t u) { return __uint_as_float(u & 0xffff0000u); }
__device__ __forceinline__ float ex2(float x) { float r; asm("ex2.approx.ftz.f32 %0, %1;" : "=f"(r) : "f"(x)); return r; }

__device__ __forceinline__ void st_pkt_if(uint32_t on, void* p, uint32_t a, uint32_t b, uint32_t c, uint32_t d) {
    asm volatile("{\n.reg .pred p;\n.reg .b64 l, h;\n.reg .b128 v;\nsetp.ne.u32 p, %5, 0;\nmov.b64 l, {%1,%2};\nmov.b64 h, {%3,%4};\nmov.b128 v, {l,h};\n"
                 "@p st.relaxed.gpu.global.b128 [%0], v;\n}" ::"l"(p), "r"(a), "r"(b), "r"(c), "r"(d), "r"(on) : "memory");
}
__device__ __forceinline__ void ld_pkt_if(uint32_t on, uint4& v, const void* p) {
    asm volatile("{\n.reg .pred p;\n.reg .b64 l, h;\n.reg .b128 v;\nsetp.ne.u32 p, %5, 0;\nmov.b64 l, {%0,%1};\nmov.b64 h, {%2,%3};\nmov.b128 v, {l,h};\n"
                 "@p ld.relaxed.gpu.global.b128 v, [%4];\nmov.b128 {l,h}, v;\nmov.b64 {%0,%1}, l;\nmov.b64 {%2,%3}, h;\n}"
                 : "+r"(v.x), "+r"(v.y), "+r"(v.z), "+r"(v.w) : "l"(p), "r"(on) : "memory");
}
__device__ __forceinline__ void st_pkt8(void* p, uint32_t a, uint32_t b) {
    asm volatile("{\n.reg .b64 v;\nmov.b64 v, {%1,%2};\nst.relaxed.gpu.global.b64 [%0], v;\n}" ::"l"(p), "r"(a), "r"(b) : "memory");
}
__device__ __forceinline__ uint2 ld_pkt8(const void* p) {
    uint2 v;
    asm volatile("{\n.reg .b64 v;\nld.relaxed.gpu.global.b64 v, [%2];\nmov.b64 {%0,%1}, v;\n}" : "=r"(v.x), "=r"(v.y) : "l"(p) : "memory");
    return v;
}
__device__ __forceinline__ void st_f4_if(uint32_t on, void* p, float a, float b, float c, float d, uint32_t tag) {
    const uint32_t ud = __float_as_uint(d);
    st_pkt_if(on, p, __byte_perm(__float_as_uint(a), ud, 0x3217), __byte_perm(__float_as_uint(b), ud, 0x3216),
              __byte_perm(__float_as_uint(c), ud, 0x3215), tag);
}
__device__ __forceinline__ float4 unpack_f4(const uint4& v) {
    const uint32_t d = __byte_perm(__byte_perm(v.z, v.y, 0x0400), v.x, 0x4210);
    return make_float4(__uint_as_float(v.x & 0xffffff00u), __uint_as_float(v.y & 0xffffff00u), __uint_as_float(v.z & 0xffffff00u), __uint_as_float(d & 0xffffff00u));
}
template <int N, int NZ, class AddrFn>
__device__ __forceinline__ void poll_pkts(uint4 (&v)[N], uint32_t (&need)[N], uint32_t tag, AddrFn addr) {
#pragma unroll
    for (int i = 0; i < N; i++) v[i] = make_uint4(0u, 0u, 0u, 0u);
    for (uint32_t n = 0;; n++) {
#pragma unroll
        for (int i = 0; i < N; i++) ld_pkt_if(need[i], v[i], addr(i));
        uint32_t any = 0;
#pragma unroll
        for (int i = 0; i < N; i++) { need[i] = ((i < NZ ? v[i].z : v[i].w) != tag) ? need[i] : 0u; any |= need[i]; }
        if (!__any_sync(0xffffffffu, any != 0)) break;
        if (n > (1u << 22)) __trap();
    }
}
template <int ID, int N> __device__ __forceinline__ void bar_sync() { asm volatile("bar.sync %0, %1;" ::"n"(ID), "n"(N) : "memory"); }
template <int ID, int N> __device__ __forceinline__ void bar_arrive() { asm volatile("bar.arrive %0, %1;" ::"n"(ID), "n"(N) : "memory"); }
constexpr int BAR_W = 1;
constexpr int BAR_GO = 2;
constexpr int BAR_ACT2 = 3;
constexpr int BAR_Q = 6;
constexpr int BAR_C = 7;
constexpr int BAR_XN = 8;
constexpr int BAR_ST = 9;
constexpr int BAR_ACT = 10;
__device__ __forceinline__ float warp_sum(float v) {
#pragma unroll
    for (int o = 16; o > 0; o >>= 1) v += __shfl_xor_sync(0xffffffffu, v, o);
    return v;
}
__device__ __forceinline__ float warp_max(float v) {
    int i = __float_as_int(v);
    i ^= (i >> 31) & 0x7fffffff;
    i = __reduce_max_sync(0xffffffffu, i);
    i ^= (i >> 31) & 0x7fffffff;
    return __int_as_float(i);
}
__device__ __forceinline__ float2 ln_stats(const float4 (&v)[5], int lane) {
    const float piv = __shfl_sync(0xffffffffu, v[0].x, 0);
    float s = 0.f, ss = 0.f;
#pragma unroll
    for (int j = 0; j < 5; j++) {
        const float a = v[j].x - piv, b = v[j].y - piv, c = v[j].z - piv, d = v[j].w - piv;
        if (j < 4 || lane < 16) { s += (a + b) + (c + d); ss += (a * a + b * b) + (c * c + d * d); }
    }
#pragma unroll
    for (int o = 16; o > 0; o >>= 1) { s += __shfl_xor_sync(0xffffffffu, s, o); ss += __shfl_xor_sync(0xffffffffu, ss, o); }
    const float dm = s * (1.0f / DM);
    const float var = bfr(fmaxf(ss * (1.0f / DM) - dm * dm, 0.f));
    float sd, rs;
    asm("sqrt.approx.f32 %0, %1;" : "=f"(sd) : "f"(bfr(var + 1e-5f)));
    asm("rcp.approx.f32 %0, %1;" : "=f"(rs) : "f"(bfr(sd)));
    return make_float2(bfr(piv + dm), rs);
}
__device__ __forceinline__ void send_tile(uint32_t on, uint4* dst, const float (&c)[4], int g, int t, uint32_t tag) {
    st_f4_if(t < 2 ? on : 0u, dst + g + 8 * t, c[0], c[1], c[2], c[3], tag);
}
template <int NSRC>
__device__ __forceinline__ void reduce_cols(uint32_t on, const uint4* src, float* s_red, int vw, int lane, uint32_t tag) {
    uint4 v[4];
    uint32_t need[4];
    const int c0 = vw * 4 + (lane >> 3);
#pragma unroll
    for (int i = 0; i < 4; i++) need[i] = (c0 + 32 * i < NSRC) ? on : 0u;
    poll_pkts<4, 0>(v, need, tag, [&](int i) { return src + (c0 + 32 * i) * DM + (lane & 7); });
    float4 a = make_float4(0.f, 0.f, 0.f, 0.f);
#pragma unroll
    for (int i = 0; i < 4; i++) { const float4 f = unpack_f4(v[i]); a.x += f.x; a.y += f.y; a.z += f.z; a.w += f.w; }
#pragma unroll
    for (int o = 8; o <= 16; o <<= 1) {
        a.x += __shfl_xor_sync(0xffffffffu, a.x, o); a.y += __shfl_xor_sync(0xffffffffu, a.y, o);
        a.z += __shfl_xor_sync(0xffffffffu, a.z, o); a.w += __shfl_xor_sync(0xffffffffu, a.w, o);
    }
    if (lane < 8) reinterpret_cast<float4*>(s_red + vw * 32)[lane] = a;
}

template <int I0, int CNT, int BAR, int NBAR>
__device__ __forceinline__ void down_tiles(uint32_t real, uint32_t sb, const uint8_t* smem, uint32_t bar_dn, uint4* dst, int w, int lane, uint32_t tag) {
    const int g = lane >> 2, t = lane & 3, id = lane >> 3, rr = lane & 7;
    uint32_t da[CNT][2][4];
    if (real) { mbar_wait(bar_dn, 0); mbar_wait(bar_dn + 8, 0); }
    const int jc = w * 2 + (id & 1);
#pragma unroll
    for (int i = 0; i < CNT; i++) {
        const uint32_t ad = sb + OFF_DN + ((id >> 1) * 8 + rr) * WROW + (I0 + i) * 128 + ((jc ^ ((rr + I0 + i) & 7)) << 4);
        ldsm4t(da[i][0], ad);
        ldsm4t(da[i][1], ad + 16 * WROW);
    }
    if (real) bar_sync<BAR, NBAR>();
    uint32_t ba[5];
    const uint32_t* s_act32 = reinterpret_cast<const uint32_t*>(smem + OFF_ACT + (g & 3) * ACT_PITCH);
#pragma unroll
    for (int k = 0; k < 5; k++) ba[k] = s_act32[k * 4 + t];
    float c[CNT][4];
#pragma unroll
    for (int i = 0; i < CNT; i++) { c[i][0] = c[i][1] = c[i][2] = c[i][3] = 0.f; mma16816(c[i], da[i][0], ba[0], ba[1]); }
#pragma unroll
    for (int i = 0; i < CNT; i++) mma16816(c[i], da[i][1], ba[2], ba[3]);
    if (real) mbar_wait(bar_dn + 16, 0);
#pragma unroll
    for (int i = 0; i < CNT; i += 2) {
        const int ci = I0 + ((i + 1 < CNT) ? i + (id >> 1) : i);
        uint32_t a2[4];
        ldsm4t(a2, sb + OFF_DN + (32 + rr) * WROW + ci * 128 + ((jc ^ ((rr + ci) & 7)) << 4));
        mma1688(c[i], a2[0], a2[1], ba[4]);
        if (i + 1 < CNT) mma1688(c[i + 1], a2[2], a2[3], ba[4]);
    }
#pragma unroll
    for (int i = 0; i < CNT; i++) send_tile(real, dst + (w + 4 * (I0 + i)) * 16, c[i], g, t, tag);
}

__device__ __forceinline__ float sum8(const float* r) {
    return ((r[0] + r[32]) + (r[64] + r[96])) + ((r[128] + r[160]) + (r[192] + r[224]));
}

__device__ __forceinline__ int oproj_role(int cta) {
    return cta < NFF - (GRID - NOP) ? cta : (cta < NFF ? -1 : cta - (GRID - NOP));
}

struct Params {
    const __nv_bfloat16* x;
    const char* k;
    const char* v;
    __nv_bfloat16* out;
};

__global__ void __launch_bounds__(NTHR, 1)
fused_decode_kernel(const Params p, const __grid_constant__ CUtensorMap tm_q, const __grid_constant__ CUtensorMap tm_o,
                    const __grid_constant__ CUtensorMap tm_gate, const __grid_constant__ CUtensorMap tm_up,
                    const __grid_constant__ CUtensorMap tm_dn) {
    extern __shared__ __align__(1024) uint8_t smem[];
    const uint32_t sb = smem_u32(smem);
    const int tid = threadIdx.x, warp = tid >> 5, lane = tid & 31, cta = blockIdx.x;
    const int g = lane >> 2, t = lane & 3, id = lane >> 3, rr = lane & 7;
    const uint32_t bar_full = sb + OFF_BAR, bar_empty = bar_full + 2 * NS * 8, bar_wq = bar_empty + NS * 8, bar_box = bar_wq + 24;
    volatile int* s_misc = reinterpret_cast<volatile int*>(smem + OFF_MISC);
    __nv_bfloat16* s_x = reinterpret_cast<__nv_bfloat16*>(smem + OFF_X);
    uint64_t pol;
    asm volatile("createpolicy.fractional.L2::evict_first.b64 %0, 1.0;" : "=l"(pol));
    auto issue_unit = [&](uint32_t u, uint32_t item) {
        const uint32_t bar = bar_full + (u & 7) * 8;
        const bool with_q = (u & 3) == 0 && u != 0;
        if ((u & 3) == 0) s_misc[2 + ((u >> 2) & 1)] = (int)item;
        mbar_expect_tx(bar, with_q ? UNIT + 512 : UNIT);
        bulk_load(sb + OFF_RING + (u & 7) * UNIT, ((u & 2) ? p.v : p.k) + (size_t)item * SLOT + (u & 1) * UNIT, UNIT, bar, pol);
        if (with_q) bulk_load_plain(sb + OFF_Q + ((u >> 2) & 1) * 512, g_q + (item / IPH) * (DH / 2), 512, bar);
    };

    if (tid == 32) {
#pragma unroll
        for (int i = 0; i < K_WKV; i++) mbar_init(bar_full + i * 8, 1);
        mbar_init(bar_wq, 1); mbar_init(bar_wq + 8, 1); mbar_init(bar_wq + 16, 1);
        asm volatile("fence.mbarrier_init.release.cluster;" ::: "memory");
        asm volatile("fence.proxy.async.shared::cta;" ::: "memory");
        if (cta < NOP) {
#pragma unroll
            for (int i = 0; i < 3; i++) {
                mbar_expect_tx(bar_wq + i * 8, 192 * 64);
                tensor_load_2d(sb + OFF_WO + i * 192 * 64, &tm_q, cta * 32, i * 192, bar_wq + i * 8);
            }
        }
#pragma unroll
        for (int u = 0; u < K_WKV; u++) issue_unit(u, cta);
    }
    if ((warp == 6 || warp == 7) && t < 2 && cta < NOP) {
        uint2* q = g_q + ((2 * t + (g & 1)) * NH + (cta >> 2)) * (DH / 2) + (cta & 3) * 16 + (warp - 6) * 8 + (g >> 1);
        st_pkt8(q, 0u, 0u);
        st_pkt8(q + 4, 0u, 0u);
    }
    if (warp >= 6) {
#pragma unroll
        for (int j = 0; j < 5; j++) if (j < 4 || lane < 16)
            reinterpret_cast<uint2*>(s_x + (warp - 6) * DM)[lane + 32 * j] = __ldg(reinterpret_cast<const uint2*>(p.x + (warp - 6) * DM) + lane + 32 * j);
    } else if (warp == 0) {
        if (lane == 31) {
            unsigned int c;
            asm volatile("ld.relaxed.gpu.global.u32 %0, [%1];" : "=r"(c) : "l"(&g_ctr_item) : "memory");
            s_misc[0] = (int)(c / NITEMS + 1);
            s_misc[1] = 0;
        } else if (lane >= K_WKV && lane < 3 * NS + 3 + NBOX && (lane < 3 * NS || lane >= 3 * NS + 3)) {
            mbar_init(bar_full + lane * 8, 1);
            asm volatile("fence.mbarrier_init.release.cluster;" ::: "memory");
        }
    }
    __syncthreads();
    const uint32_t tag = (uint32_t)s_misc[0];

    if (warp == 0) {
        uint32_t offK[4], offV[4];
#pragma unroll
        for (int j = 0; j < 4; j++) {
            offK[j] = sb + OFF_RING + ((id & 1) * 8 + rr) * 256 + (((2 * j + (id >> 1)) ^ rr) << 4);
            offV[j] = sb + OFF_RING + ((id >> 1) * 8 + rr) * 256 + (((2 * j + (id & 1)) ^ rr) << 4);
        }
        const bool valid = (t == (g >> 1));
        const int odd = g & 1;
        const uint32_t sel0 = !valid ? 0x4444u : (odd ? 0x1044u : 0x4410u), sel1 = !valid ? 0x4444u : (odd ? 0x3244u : 0x4432u);
        static_assert(MT == 8, "max tree");
        const float SCALE = 0.08838834764831845f, LOG2E = 1.4426950408889634f;
        for (uint32_t n = 0;; n++) {
            const uint32_t u0 = (n & 1) * 4, ph = (n >> 1) & 1;
            mbar_wait(bar_full + u0 * 8, ph);
            const uint32_t it0 = (uint32_t)s_misc[2 + (n & 1)];
            if (it0 >= (uint32_t)NITEMS) break;
            uint2 qn[2];
            qn[0] = *reinterpret_cast<const uint2*>(smem + OFF_Q + (n & 1) * 512 + lane * 8);
            qn[1] = *reinterpret_cast<const uint2*>(smem + OFF_Q + (n & 1) * 512 + 256 + lane * 8);
            if (n == 0) qn[0].y = 0;
            for (uint32_t k = 0; __any_sync(0xffffffffu, qn[0].y != tag || qn[1].y != tag); k++) {
                if (k > (1u << 22)) __trap();
                const uint2* qp = g_q + (it0 / IPH) * (DH / 2) + lane;
                qn[0] = ld_pkt8(qp); qn[1] = ld_pkt8(qp + 32);
            }
            uint32_t qf[16];
#pragma unroll
            for (int c = 0; c < 16; c++) qf[c] = __shfl_sync(0xffffffffu, qn[c >> 3].x, (((c & 7) ^ g) << 2) + t);
            mbar_wait(bar_full + (u0 + 1) * 8, ph);
            float sc[MT][4];
#pragma unroll
            for (int m = 0; m < MT; m++) { sc[m][0] = sc[m][1] = sc[m][2] = sc[m][3] = 0.f; }
            {
                const uint32_t so = u0 * UNIT;
#pragma unroll
                for (int j = 0; j < 8; j++) {
#pragma unroll
                    for (int m = 0; m < MT; m++) {
                        uint32_t a[4];
                        ldsm4(a, offK[j & 3] + so + m * 4096 + (j >> 2) * 128);
                        mma16816(sc[m], a, qf[2 * j], qf[2 * j + 1]);
                    }
                }
            }
            __syncwarp();
            if (lane == 0) mbar_arrive(bar_empty + (u0 >> 1) * 8);
            uint32_t sp[MT];
#pragma unroll
            for (int m = 0; m < MT; m++) {
                const uint32_t r = pack_bf16(odd ? sc[m][1] : sc[m][0], odd ? sc[m][3] : sc[m][2]);
                sp[m] = pack_bf16(bf_lo(r) * SCALE, bf_hi(r) * SCALE);
            }
            const uint32_t m2 = max_bf16x2(max_bf16x2(max_bf16x2(sp[0], sp[1]), max_bf16x2(sp[2], sp[3])), max_bf16x2(max_bf16x2(sp[4], sp[5]), max_bf16x2(sp[6], sp[7])));
            const float mx = warp_max(valid ? fmaxf(bf_lo(m2), bf_hi(m2)) : -INFINITY);
            const float nb = (mx == -INFINITY) ? 0.f : -mx * LOG2E;
            float l0 = 0.f, l1 = 0.f;
            uint32_t pb[2 * MT];
#pragma unroll
            for (int m = 0; m < MT; m++) {
                const float e0 = ex2(fmaf(bf_lo(sp[m]), LOG2E, nb)), e1 = ex2(fmaf(bf_hi(sp[m]), LOG2E, nb));
                l0 += e0; l1 += e1;
                const uint32_t pk = pack_bf16(e0, e1);
                pb[2 * m] = __byte_perm(pk, 0u, sel0);
                pb[2 * m + 1] = __byte_perm(pk, 0u, sel1);
            }
            const float l = warp_sum(valid ? l0 + l1 : 0.f);
            st_pkt_if(lane == 0, &g_ml[it0], __float_as_uint(mx), __float_as_uint(l), tag, 0u);
            float acc[8][4];
#pragma unroll
            for (int i = 0; i < 8; i++) { acc[i][0] = acc[i][1] = acc[i][2] = acc[i][3] = 0.f; }
            {
                const uint32_t so = (u0 + 2) * UNIT;
#pragma unroll
                for (int m = 0; m < MT; m++) {
                    if (m % (MT / 2) == 0) mbar_wait(bar_full + (u0 + 2 + m / (MT / 2)) * 8, ph);
#pragma unroll
                    for (int i = 0; i < 8; i++) {
                        uint32_t a[4];
                        ldsm4t(a, offV[i & 3] + so + m * 4096 + (i >> 2) * 128);
                        mma16816(acc[i], a, pb[2 * m], pb[2 * m + 1]);
                    }
                }
            }
            __syncwarp();
            if (lane == 0) mbar_arrive(bar_empty + ((u0 >> 1) + 1) * 8);
            float T[16];
#pragma unroll
            for (int i = 0; i < 8; i++) { T[2 * i] = acc[i][0] + acc[i][3]; T[2 * i + 1] = acc[i][2] + acc[i][1]; }
            float U[16];
#pragma unroll
            for (int c = 0; c < 16; c++) if (!(c & 2)) U[c] = T[c] + __shfl_xor_sync(0xffffffffu, T[c ^ 2], 1);
            const float y0 = U[0] + __shfl_xor_sync(0xffffffffu, U[4], 2), y1 = U[1] + __shfl_xor_sync(0xffffffffu, U[5], 2);
            const float y2 = U[8] + __shfl_xor_sync(0xffffffffu, U[12], 2), y3 = U[9] + __shfl_xor_sync(0xffffffffu, U[13], 2);
            st_f4_if(1u, g_op + (size_t)it0 * 32 + t * 8 + g, y0, y1, y2, y3, tag);
        }
        if (cta >= NFF) return;
    } else if (warp == 1) {
        if (lane == 0) {
            asm volatile("prefetch.tensormap [%0];" ::"l"(&tm_o) : "memory");
            asm volatile("prefetch.tensormap [%0];" ::"l"(&tm_gate) : "memory");
            asm volatile("prefetch.tensormap [%0];" ::"l"(&tm_up) : "memory");
            asm volatile("prefetch.tensormap [%0];" ::"l"(&tm_dn) : "memory");
        }
        uint32_t item = cta, pend = 0, u = K_WKV;
        auto claim = [&]() {
            asm volatile("{\n.reg .pred p;\nsetp.eq.u32 p, %2, 0;\n@p atom.relaxed.gpu.global.add.u32 %0, [%1], 1;\n}" : "+r"(pend) : "l"(&g_ctr_item + lane), "r"(lane) : "memory");
        };
        claim();
        for (;; u++) {
            if (!(u & 1)) {
                mbar_wait(bar_full + ((u - K_WKV) & 7) * 8, ((u - K_WKV) >> 3) & 1);
                mbar_wait(bar_full + ((u - K_WKV + 1) & 7) * 8, ((u - K_WKV + 1) >> 3) & 1);
                if (u >= 2 * NS) mbar_wait(bar_empty + ((u >> 1) & 3) * 8, ((u >> 3) - 1) & 1);
            }
            if ((u & 3) == 0) {
                item = __shfl_sync(0xffffffffu, pend, 0) % NITEMS + GRID;
                if (item >= (uint32_t)NITEMS) break;
            }
            if (lane == 0) issue_unit(u, item);
            if ((u & 3) == K_CLAIM) claim();
            __syncwarp();
        }
        if (lane == 0) {
            s_misc[2 + ((u >> 2) & 1)] = NITEMS;
            s_misc[1] = (int)((u >> 1) & 3);
            mbar_arrive(bar_full + (u & 7) * 8);
        }
        __syncwarp();
        bar_arrive<BAR_GO, 288>();
        const int slot0 = (u >> 1) & 3, opr = oproj_role(cta);
        const int box0 = opr >= 0 ? 0 : 2, nbox = cta < NFF ? NBOX : 2;
#pragma unroll
        for (int i = 0; i < NBOX; i++) {
            const int pc = (i - 2) >> 1;
            if (i >= box0 && i < nbox) {
                if (i >= 4 && i < BOX_DN && !(i & 1)) mbar_wait(bar_empty + ((slot0 + pc) & 3) * 8, ((u + 2 * pc) / 8 - 1) & 1);
                const int win = i < K_J ? K_WIN : K_WIN2;
                if (i >= box0 + win) mbar_wait(bar_box + (i - win) * 8, 0);
                if (i - box0 < K_HOLD) { const uint32_t w = u + (i - box0) - K_HOLD; mbar_wait(bar_full + (w & 7) * 8, (w >> 3) & 1); }
                if (lane == 0) {
                    const uint32_t bar = bar_box + i * 8;
                    if (i < 2) {
                        mbar_expect_tx(bar, 16 * WROW);
                        const int r0 = (opr >> 2) * DH + (opr & 3) * 16 + i * 64;
                        tensor_load_3d(sb + OFF_WO + i * 16 * WROW, &tm_o, r0, bar, pol);
                        tensor_load_3d(sb + OFF_WO + (i * 16 + 8) * WROW, &tm_o, r0 + 8, bar, pol);
                    } else if (i < BOX_DN) {
                        mbar_expect_tx(bar, GU_BOX);
                        tensor_load_2d(sb + OFF_RING + ((slot0 + pc) & 3) * SLOT + (i & 1) * GU_BOX, (i & 1) ? &tm_up : &tm_gate, cta * FC - (cta & 1) * 8, pc * GU_ROWS, bar);
                    } else {
                        const int r0 = (i - BOX_DN) * 16;
                        mbar_expect_tx(bar, (i < BOX_DN + 2 ? 16 : 8) * WROW);
                        tensor_load_3d(sb + OFF_DN + r0 * WROW, &tm_dn, cta * FC + r0, bar, pol);
                        if (i < BOX_DN + 2) tensor_load_3d(sb + OFF_DN + (r0 + 8) * WROW, &tm_dn, cta * FC + r0 + 8, bar, pol);
                    }
                }
                __syncwarp();
            }
        }
        return;
    }

    const int vw = (warp == 0) ? 8 : warp - 2, wt = tid - 64;
    if (vw >= 4 && vw < 8 && cta < NOP) {
        const int w2 = vw - 4;
        float4 xv[5];
#pragma unroll
        for (int j = 0; j < 5; j++) {
            const uint2 u = reinterpret_cast<const uint2*>(s_x + w2 * DM)[(j < 4 || lane < 16) ? lane + 32 * j : lane];
            xv[j] = make_float4(bf_lo(u.x), bf_hi(u.x), bf_lo(u.y), bf_hi(u.y));
        }
        const float2 st = ln_stats(xv, lane);
#pragma unroll
        for (int j = 0; j < 5; j++) {
            uint2 o;
            o.x = pack_bf16(bfr(xv[j].x - st.x) * st.y, bfr(xv[j].y - st.x) * st.y);
            o.y = pack_bf16(bfr(xv[j].z - st.x) * st.y, bfr(xv[j].w - st.x) * st.y);
            if (j < 4 || lane < 16) *reinterpret_cast<uint2*>(smem + OFF_XN + w2 * WPITCH + (lane + 32 * j) * 8) = o;
        }
        bar_sync<BAR_Q, 128>();
        if (w2 < 2) {
            float c[4][4];
#pragma unroll
            for (int i = 0; i < 4; i++) { c[i][0] = c[i][1] = c[i][2] = c[i][3] = 0.f; }
            const uint32_t bbase = sb + OFF_XN + (rr & 3) * WPITCH + id * 16;
            const uint32_t abase = sb + OFF_WO + ((id >> 1) * 8 + rr) * 64 + (((2 * w2 + (id & 1)) ^ (rr >> 1)) << 4);
#pragma unroll 1
            for (int bx = 0; bx < 3; bx++) {
                mbar_wait(bar_wq + bx * 8, 0);
#pragma unroll
                for (int k2 = 0; k2 < 6; k2++) {
                    uint32_t bf[4], a0[4], a1[4];
                    ldsm4(bf, bbase + (bx * 6 + k2) * 64);
                    ldsm4t(a0, abase + (bx * 6 + k2) * 2048);
                    ldsm4t(a1, abase + (bx * 6 + k2) * 2048 + 1024);
                    mma16816(c[(2 * k2) & 3], a0, bf[0], bf[1]);
                    mma16816(c[(2 * k2 + 1) & 3], a1, bf[2], bf[3]);
                }
            }
            const bool od = g & 1;
            const float v0 = (c[0][0] + c[1][0]) + (c[2][0] + c[3][0]), v1 = (c[0][1] + c[1][1]) + (c[2][1] + c[3][1]);
            const float v2 = (c[0][2] + c[1][2]) + (c[2][2] + c[3][2]), v3 = (c[0][3] + c[1][3]) + (c[2][3] + c[3][3]);
            const float r0 = __shfl_xor_sync(0xffffffffu, od ? v0 : v1, 4), r1 = __shfl_xor_sync(0xffffffffu, od ? v2 : v3, 4);
            if (t < 2) {
                uint2* q = g_q + ((2 * t + (g & 1)) * NH + (cta >> 2)) * (DH / 2) + (cta & 3) * 16 + w2 * 8 + (g >> 1);
                st_pkt8(q, od ? pack_bf16(r0, v1) : pack_bf16(v0, r0), tag);
                st_pkt8(q + 4, od ? pack_bf16(r1, v3) : pack_bf16(v2, r1), tag);
            }
        }
    }
    float* s_comb = reinterpret_cast<float*>(smem + OFF_COMB);
    float* s_red = reinterpret_cast<float*>(smem + OFF_RED);
#pragma unroll 1
    for (uint32_t pass = (vw == 8) ? 1u : 0u; pass < 2; pass++) {
        uint32_t real;
        asm volatile("mov.u32 %0, %1;" : "=r"(real) : "r"(pass));
        int lane, cid;
        asm volatile("mov.u32 %0, %laneid;" : "=r"(lane));
        asm volatile("mov.u32 %0, %ctaid.x;" : "=r"(cid));
        const int g = lane >> 2, t = lane & 3, id = lane >> 3, rr = lane & 7;
        if (vw < 8) {
            const int opr = oproj_role(cid);
            if (real) {
                for (int n = wt; n < DM; n += 256) {
                    st_pkt_if(opr >= 0, g_p1 + opr * DM + n, 0u, 0u, 0u, 0u);
                    st_pkt_if(cid < NFF, g_p2 + cid * DM + n, 0u, 0u, 0u, 0u);
                }
                if (vw == 0) {
#pragma unroll
                    for (int r = 0; r < (HREP + 3) / 4; r++)
                        st_pkt_if(4 * r + t < HREP && cid < NRED, g_h + ((4 * r + t) * NB + (cid & 1) * 2 + (lane >> 4)) * (DM / 4) + (cid >> 1) * 4 + (g & 3), 0u, 0u, 0u, 0u);
                }
                bar_sync<BAR_GO, 288>();
            } else bar_sync<BAR_W, 256>();
            if (opr >= 0) {
                constexpr int PW = IPH / 2;
                constexpr int NML = IPH / 32, NOV = PW / 4;
                const int half = vw & 1;
                const int base = ((vw >> 1) * NH + (opr >> 2)) * IPH;
                uint4 pk[NML + NOV];
                {
                    uint32_t need[NML + NOV];
#pragma unroll
                    for (int i = 0; i < NML + NOV; i++) need[i] = real;
                    const uint4* pml = g_ml + base + lane;
                    const uint4* pov = g_op + (size_t)(base + half * PW + id) * 32 + (opr & 3) * 8 + rr;
                    poll_pkts<NML + NOV, NML>(pk, need, tag, [&](int i) { return i < NML ? pml + i * 32 : pov + (i - NML) * 128; });
                }
                float M = __uint_as_float(pk[0].x);
#pragma unroll
                for (int i = 1; i < NML; i++) M = fmaxf(M, __uint_as_float(pk[i].x));
                M = warp_max(M);
                float wgt[NML], L = 0.f;
#pragma unroll
                for (int i = 0; i < NML; i++) { wgt[i] = ex2((__uint_as_float(pk[i].x) - M) * 1.4426950408889634f); L += wgt[i] * __uint_as_float(pk[i].y); }
                float4 a = make_float4(0.f, 0.f, 0.f, 0.f);
#pragma unroll
                for (int i = 0; i < NOV; i++) {
                    const int j = i * 4;
                    const float wsel = half ? wgt[(PW + j) / 32] : wgt[j / 32];
                    const float w = __shfl_sync(0xffffffffu, wsel, ((half * PW + j) & 31) + id);
                    const float4 o4 = unpack_f4(pk[NML + i]);
                    a.x = fmaf(w, o4.x, a.x); a.y = fmaf(w, o4.y, a.y); a.z = fmaf(w, o4.z, a.z); a.w = fmaf(w, o4.w, a.w);
                }
                L = warp_sum(L);
#pragma unroll
                for (int o = 8; o <= 16; o <<= 1) {
                    a.x += __shfl_xor_sync(0xffffffffu, a.x, o); a.y += __shfl_xor_sync(0xffffffffu, a.y, o);
                    a.z += __shfl_xor_sync(0xffffffffu, a.z, o); a.w += __shfl_xor_sync(0xffffffffu, a.w, o);
                }
                const float inv = __fdividef(1.0f, L);
                if (lane < 8) reinterpret_cast<float4*>(s_comb + vw * 32)[lane] = make_float4(a.x * inv, a.y * inv, a.z * inv, a.w * inv);
                if (vw < 6) {
                    uint32_t wa[6][2][4];
                    if (real) { mbar_wait(bar_box, 0); mbar_wait(bar_box + 8, 0); }
#pragma unroll
                    for (int i = 0; i < 6; i++) {
                        const int mt = vw + 6 * i;
                        const uint32_t ad = sb + OFF_WO + ((id >> 1) * 8 + rr) * WROW + (mt >> 2) * 128 + ((((mt & 3) * 2 + (id & 1)) ^ ((rr + (mt >> 2)) & 7)) << 4);
                        ldsm4t(wa[i][0], ad);
                        ldsm4t(wa[i][1], ad + 16 * WROW);
                    }
                    if (real) bar_sync<BAR_C, 256>();
                    const float4* c0 = reinterpret_cast<const float4*>(s_comb + (g & 3) * 64) + 2 * t;
                    const float4 u0 = c0[0], u1 = c0[1], v0 = c0[8], v1 = c0[9];
                    const uint32_t bo0 = pack_bf16(u0.x + v0.x, u1.x + v1.x), bo1 = pack_bf16(u0.y + v0.y, u1.y + v1.y);
                    const uint32_t bo2 = pack_bf16(u0.z + v0.z, u1.z + v1.z), bo3 = pack_bf16(u0.w + v0.w, u1.w + v1.w);
                    float c[6][4];
#pragma unroll
                    for (int i = 0; i < 6; i++) { c[i][0] = c[i][1] = c[i][2] = c[i][3] = 0.f; mma16816(c[i], wa[i][0], bo0, bo1); }
#pragma unroll
                    for (int i = 0; i < 6; i++) mma16816(c[i], wa[i][1], bo2, bo3);
#pragma unroll
                    for (int i = 0; i < 6; i++) send_tile(real, g_p1 + opr * DM + (vw + 6 * i) * 16, c[i], g, t, tag);
                } else {
                    __syncwarp();
                    if (real) bar_arrive<BAR_C, 256>();
                }
            }
            if (cid >= NFF) continue;
            if (cid < NRED) {
                reduce_cols<NOP>(real, g_p1 + cid * 8, s_red, vw, lane, tag);
                if (real) bar_sync<BAR_W, 256>();
                if (vw == 0) {
                    const int ob = (cid & 1) * 2 + (lane >> 4), oc = (cid >> 1) * 16 + (lane & 15);
                    const float a1 = sum8(s_red + rr * 4 + (id & 1) * 2 + (id >> 1));
                    const float h = __bfloat162float(s_x[ob * DM + oc]) + bfr(a1);
                    const uint32_t u = pack_bf16(h, __shfl_down_sync(0xffffffffu, h, 1));
                    const uint32_t u0 = __shfl_sync(0xffffffffu, u, lane & ~3), u2 = __shfl_sync(0xffffffffu, u, (lane & ~3) + 2);
#pragma unroll
                    for (int r = 0; r < (HREP + 3) / 4; r++)
                        st_pkt_if(4 * r + t < HREP ? real : 0u, g_h + ((4 * r + t) * NB + ob) * (DM / 4) + (oc >> 2), u0, u2, tag, 0u);
                }
            }
        }
        if (vw < 4 || vw == 8) {
            const int ct = (vw == 8) ? 4 : vw;
            constexpr int KS = GU_ROWS / 16;
            constexpr int NPRE = 32;
            uint32_t ga[NPRE][4];
            uint32_t alast = 0;
            const uint32_t aoff = sb + OFF_RING + (id & 1) * GU_BOX + ((id >> 1) * 8 + rr) * (GW * 2) + ct * 16 + (cid & 1) * 16;
            int sl = s_misc[1];
#pragma unroll
            for (int pc = 0; pc < GU_PIECES; pc++) {
                if (real) { mbar_wait(bar_box + (2 + 2 * pc) * 8, 0); mbar_wait(bar_box + (3 + 2 * pc) * 8, 0); }
                alast = aoff + sl * SLOT;
#pragma unroll
                for (int k = 0; k < KS; k++) if (pc * KS + k < NPRE) ldsm4t(ga[pc * KS + k], alast + k * 16 * GW * 2);
                sl = (sl + 1) & 3;
            }
            float cs[2][4] = {{0.f, 0.f, 0.f, 0.f}, {0.f, 0.f, 0.f, 0.f}};
#pragma unroll
            for (int k = 0; k < DM / 16; k++) {
                if (k < NPRE) mma16816(cs[k & 1], ga[k < NPRE ? k : 0], 0x3f803f80u, 0x3f803f80u);
                else { uint32_t al[4]; ldsm4t(al, alast + (k - (GU_PIECES - 1) * KS) * 16 * GW * 2); mma16816(cs[k & 1], al, 0x3f803f80u, 0x3f803f80u); }
            }
            const float csg = cs[0][0] + cs[1][0], csu = cs[0][2] + cs[1][2];
            if (real) bar_sync<BAR_XN, 288>();
            float cc[4][4];
#pragma unroll
            for (int i = 0; i < 4; i++) { cc[i][0] = cc[i][1] = cc[i][2] = cc[i][3] = 0.f; }
            const uint32_t bbase = sb + OFF_XN + (rr & 3) * WPITCH + (rr >> 2) * 64 + id * 16;
#pragma unroll
            for (int k4 = 0; k4 < DM / 64; k4++) {
                uint32_t bf[4];
                ldsm4(bf, bbase + k4 * 128);
#pragma unroll
                for (int j = 0; j < 4; j++) {
                    const int k = 4 * k4 + j;
                    if (k < NPRE) mma16816(cc[j], ga[k < NPRE ? k : 0], bf[2 * (j & 1)], bf[2 * (j & 1) + 1]);
                    else { uint32_t al[4]; ldsm4t(al, alast + (k - (GU_PIECES - 1) * KS) * 16 * GW * 2); mma16816(cc[j], al, bf[2 * (j & 1)], bf[2 * (j & 1) + 1]); }
                }
            }
            float c[4];
#pragma unroll
            for (int e = 0; e < 4; e++) c[e] = (cc[0][e] + cc[1][e]) + __shfl_xor_sync(0xffffffffu, cc[2][e] + cc[3][e], 2);
            if (real) bar_sync<BAR_ST, 288>();
            if (t < 2) {
                __nv_bfloat16* s_act = reinterpret_cast<__nv_bfloat16*>(smem + OFF_ACT);
                const float4 st4 = reinterpret_cast<const float4*>(s_comb + 256)[t];
#pragma unroll
                for (int e = 0; e < 2; e++) {
                    const float mb = e ? st4.z : st4.x, rs = e ? st4.w : st4.y;
                    const float gg = bfr((c[e] - mb * csg) * rs), uu = bfr((c[2 + e] - mb * csu) * rs);
                    const float ge = bfr(__fdividef(gg, 1.0f + ex2(gg * fmaf(gg * gg, -0.10294324f, -2.3022082f))));
                    s_act[(2 * t + e) * (ACT_PITCH / 2) + ct * 8 + g] = __float2bfloat16_rn(ge * uu);
                }
            }
            __syncwarp();
            if (real) bar_arrive<BAR_ACT, 288>();
            if (vw == 8) { bar_arrive<BAR_ACT2, 160>(); return; }
            down_tiles<6, 3, BAR_ACT2, 160>(real, sb, smem, bar_box + BOX_DN * 8, g_p2 + cid * DM, vw, lane, tag);
        } else {
            const int lw = vw - 4;
            uint4 hp[5];
            uint32_t need[5];
#pragma unroll
            for (int j = 0; j < 5; j++) need[j] = (j < 4 || lane < 16) ? real : 0u;
            poll_pkts<5, 5>(hp, need, tag, [&](int j) { return g_h + ((cid % HREP) * NB + lw) * (DM / 4) + lane + 32 * j; });
#pragma unroll
            for (int j = 0; j < 5; j++)
                if (j < 4 || lane < 16) *reinterpret_cast<uint2*>(smem + OFF_XN + lw * WPITCH + (lane + 32 * j) * 8) = make_uint2(hp[j].x, hp[j].y);
            __syncwarp();
            if (real) bar_arrive<BAR_XN, 288>();
            float4 hv[5];
#pragma unroll
            for (int j = 0; j < 5; j++) hv[j] = make_float4(bf_lo(hp[j].x), bf_hi(hp[j].x), bf_lo(hp[j].y), bf_hi(hp[j].y));
            const float2 st = ln_stats(hv, lane);
            if (lane == 0) reinterpret_cast<float2*>(s_comb + 256)[lw] = st;
            __syncwarp();
            if (real) bar_arrive<BAR_ST, 288>();
#pragma unroll
            for (int j = 0; j < 5; j++) if (real && (j < 4 || lane < 16)) reinterpret_cast<uint2*>(s_x + lw * DM)[lane + 32 * j] = make_uint2(hp[j].x, hp[j].y);
            down_tiles<0, 6, BAR_ACT, 288>(real, sb, smem, bar_box + BOX_DN * 8, g_p2 + cid * DM, lw, lane, tag);
        }
        if (cid < NRED) {
            reduce_cols<NFF>(real, g_p2 + cid * 8, s_red, vw, lane, tag);
            if (real) bar_sync<BAR_W, 256>();
            if (vw == 0) {
                const int ob = (cid & 1) * 2 + (lane >> 4), oc = (cid >> 1) * 16 + (lane & 15);
                const float a = sum8(s_red + rr * 4 + (id & 1) * 2 + (id >> 1));
                if (real) p.out[ob * DM + oc] = __float2bfloat16_rn(__bfloat162float(s_x[ob * DM + oc]) + bfr(a));
            }
        }
    }
}

typedef CUresult (*EncodeTiledFn)(CUtensorMap*, CUtensorMapDataType, cuuint32_t, void*, const cuuint64_t*, const cuuint64_t*,
                                  const cuuint32_t*, const cuuint32_t*, CUtensorMapInterleave, CUtensorMapSwizzle,
                                  CUtensorMapL2promotion, CUtensorMapFloatOOBfill);

}

extern "C" void kernel_launch(void* const* d_in, const int* in_sizes, int n_in, void* d_out, int out_size) {
    (void)in_sizes; (void)n_in; (void)out_size;
    static EncodeTiledFn encode = nullptr;
    if (!encode) {
        void* fn = nullptr;
        cudaDriverEntryPointQueryResult qr;
        cudaGetDriverEntryPoint("cuTensorMapEncodeTiled", &fn, cudaEnableDefault, &qr);
        encode = (EncodeTiledFn)fn;
        cudaFuncSetAttribute(fused_decode_kernel, cudaFuncAttributeMaxDynamicSharedMemorySize, SMEM_BYTES);
    }
    CUtensorMap tmq, tmo, tmg, tmu, tmd;
    const cuuint32_t estr[3] = {1, 1, 1};
    {
        const cuuint64_t gdim[2] = {(cuuint64_t)(NH * DH), (cuuint64_t)DM};
        const cuuint64_t gstr[1] = {(cuuint64_t)(NH * DH) * 2};
        const cuuint32_t box[2] = {32, 192};
        encode(&tmq, CU_TENSOR_MAP_DATA_TYPE_BFLOAT16, 2, d_in[3], gdim, gstr, box, estr, CU_TENSOR_MAP_INTERLEAVE_NONE,
               CU_TENSOR_MAP_SWIZZLE_64B, CU_TENSOR_MAP_L2_PROMOTION_L2_256B, CU_TENSOR_MAP_FLOAT_OOB_FILL_NONE);
    }
    {
        const cuuint64_t gdim[2] = {(cuuint64_t)DF, (cuuint64_t)DM};
        const cuuint64_t gstr[1] = {(cuuint64_t)DF * 2};
        const cuuint32_t box[2] = {(cuuint32_t)GW, (cuuint32_t)GU_ROWS};
        encode(&tmg, CU_TENSOR_MAP_DATA_TYPE_BFLOAT16, 2, d_in[6], gdim, gstr, box, estr, CU_TENSOR_MAP_INTERLEAVE_NONE,
               CU_TENSOR_MAP_SWIZZLE_NONE, CU_TENSOR_MAP_L2_PROMOTION_L2_128B, CU_TENSOR_MAP_FLOAT_OOB_FILL_NONE);
        encode(&tmu, CU_TENSOR_MAP_DATA_TYPE_BFLOAT16, 2, d_in[7], gdim, gstr, box, estr, CU_TENSOR_MAP_INTERLEAVE_NONE,
               CU_TENSOR_MAP_SWIZZLE_NONE, CU_TENSOR_MAP_L2_PROMOTION_L2_128B, CU_TENSOR_MAP_FLOAT_OOB_FILL_NONE);
    }
    {
        const cuuint64_t gstr[2] = {128, (cuuint64_t)WROW};
        const cuuint64_t gdo[3] = {64, 9, (cuuint64_t)(NH * DH)}, gdd[3] = {64, 9, (cuuint64_t)DF};
        const cuuint32_t box[3] = {64, 9, 8};
        encode(&tmo, CU_TENSOR_MAP_DATA_TYPE_BFLOAT16, 3, d_in[4], gdo, gstr, box, estr, CU_TENSOR_MAP_INTERLEAVE_NONE,
               CU_TENSOR_MAP_SWIZZLE_128B, CU_TENSOR_MAP_L2_PROMOTION_L2_128B, CU_TENSOR_MAP_FLOAT_OOB_FILL_NONE);
        encode(&tmd, CU_TENSOR_MAP_DATA_TYPE_BFLOAT16, 3, d_in[8], gdd, gstr, box, estr, CU_TENSOR_MAP_INTERLEAVE_NONE,
               CU_TENSOR_MAP_SWIZZLE_128B, CU_TENSOR_MAP_L2_PROMOTION_L2_128B, CU_TENSOR_MAP_FLOAT_OOB_FILL_NONE);
    }
    Params p;
    p.x = (const __nv_bfloat16*)d_in[0];
    p.k = (const char*)d_in[1];
    p.v = (const char*)d_in[2];
    p.out = (__nv_bfloat16*)d_out;
    fused_decode_kernel<<<GRID, NTHR, SMEM_BYTES, cudaStreamPerThread>>>(p, tmq, tmo, tmg, tmu, tmd);
}
```
